```python
import torch

def _softmax(x, axis=-1):
    return torch.softmax(x, dim=axis)

def _gelu(x):
    return torch.nn.functional.gelu(x, approximate='tanh')

def _silu(x):
    return torch.nn.functional.silu(x)

def _sigmoid(x):
    return torch.sigmoid(x)

def _layernorm(x, axis=-1, eps=1e-05):
    m = x.mean(dim=axis, keepdim=True)
    v = x.var(dim=axis, keepdim=True, unbiased=False)
    return (x - m) / torch.sqrt(v + eps)

def _scatter_add(tgt, idx, src, axis=0):
    return tgt.clone().index_add_(axis, idx, src)

def _segment_sum(src, seg, n):
    out = torch.zeros((n,) + src.shape[1:], dtype=src.dtype)
    return out.index_add_(0, seg, src)

def _pad(x, pw):
    flat = tuple((v for pair in reversed(pw) for v in pair))
    return torch.nn.functional.pad(x, flat)
kernel_name = 'standalone__tree_speculative_verify_tree_attention_over_candidate_token_tree__decode'

def setup_inputs():

    _w = lambda a: (lambda t: t.to(torch.bfloat16) if t.is_floating_point() else t)(torch.as_tensor(a))
    B, Hq, Hkv, T, C, D = (8, 32, 8, 1, 8192, 128)
    tree_mask = torch.zeros((B, T, T), dtype=float)
    for b in range(B):
        parent = torch.zeros(T, dtype=torch.int64)
        for i in range(1, T):
            parent[i] = int(torch.randint(0, i, (1,)).item())
        for i in range(T):
            j = i
            tree_mask[b, i, j] = 1.0
            while j > 0:
                j = parent[j]
                tree_mask[b, i, j] = 1.0
    return {'q': _w((lambda *s: torch.randn(*s, dtype=torch.bfloat16) * 0.8)(B, Hq, T, D)), 'k_cache': _w((lambda *s: torch.randn(*s, dtype=torch.bfloat16) * 0.8)(B, Hkv, C, D)), 'v_cache': _w((lambda *s: torch.randn(*s, dtype=torch.bfloat16) * 0.05)(B, Hkv, C, D)), 'k_tree': _w((lambda *s: torch.randn(*s, dtype=torch.bfloat16) * 0.8)(B, Hkv, T, D)), 'v_tree': _w((lambda *s: torch.randn(*s, dtype=torch.bfloat16) * 0.05)(B, Hkv, T, D)), 'tree_mask': _w(tree_mask)}

def reference(q, k_cache, v_cache, k_tree, v_tree, tree_mask):
    B, Hq, T, D = q.shape
    Hkv, C = (k_cache.shape[1], k_cache.shape[2])
    rep = Hq // Hkv
    kc = (lambda x, n, axis: torch.repeat_interleave(x, n, dim=axis))(k_cache, rep, axis=1)
    vc = (lambda x, n, axis: torch.repeat_interleave(x, n, dim=axis))(v_cache, rep, axis=1)
    kt = (lambda x, n, axis: torch.repeat_interleave(x, n, dim=axis))(k_tree, rep, axis=1)
    vt = (lambda x, n, axis: torch.repeat_interleave(x, n, dim=axis))(v_tree, rep, axis=1)
    k = torch.concatenate([kc, kt], axis=2)
    v = torch.concatenate([vc, vt], axis=2)
    scale = D ** (-0.5)
    scores = torch.einsum('bhqd,bhkd->bhqk', q, k) * scale
    ctx_mask = torch.ones((B, 1, T, C), dtype=scores.dtype)
    tm = tree_mask[:, None, :, :].clone()
    full_mask = torch.concatenate([ctx_mask, tm], axis=-1)
    scores = scores + (1.0 - full_mask) * -1000000000.0
    p = _softmax(scores, axis=-1)
    return torch.einsum('bhqk,bhkd->bhqd', p, v)
```

```cpp
#include <cuda_runtime.h>
#include <cuda_bf16.h>
#include <cuda.h>
#include <stdint.h>

namespace {

constexpr int kB = 8, kHq = 32, kHkv = 8, kC = 8192, kD = 128;
constexpr int kRep = kHq / kHkv;
constexpr int kTileKeys = 128;
constexpr int kTileBytes = kTileKeys * kD * 2;
#define STAGES 5
constexpr int kStages = STAGES;
constexpr int kKeysPerCta = kC / 2;
constexpr int kTiles = kKeysPerCta / kTileKeys;
constexpr int kConsumerWarps = 8;
constexpr int kThreads = 32 * (kConsumerWarps + 1);
constexpr int kPitch = kKeysPerCta * 2 + 16;

constexpr int kOffRing = 0;
constexpr int kOffP = kOffRing + kStages * kTileBytes;
constexpr int kOffX = kOffP + kRep * kPitch;
constexpr int kOffWmax = kOffX + 2048;
constexpr int kOffStatL = kOffWmax + 64;
constexpr int kOffStatR = kOffStatL + 64;
constexpr int kOffTree = kOffStatR + 64;
constexpr int kOffBar = kOffTree + 16;
constexpr int kSmemUsed = kOffBar + 8 * (2 * kStages + 2);
constexpr int kSmemBytes = kSmemUsed + 1024;

constexpr float kScale = 0.08838834764831845f;
constexpr float kLog2e = 1.4426950408889634f;

__device__ __forceinline__ uint32_t smem_u32(const void* p) { return (uint32_t)__cvta_generic_to_shared(p); }
__device__ __forceinline__ void mbar_init(uint32_t bar, int cnt) {
    asm volatile("mbarrier.init.shared::cta.b64 [%0], %1;" ::"r"(bar), "r"(cnt) : "memory");
}
__device__ __forceinline__ void mbar_expect_tx(uint32_t bar, uint32_t bytes) {
    asm volatile("mbarrier.arrive.expect_tx.shared::cta.b64 _, [%0], %1;" ::"r"(bar), "r"(bytes) : "memory");
}
__device__ __forceinline__ void mbar_arrive(uint32_t bar) {
    asm volatile("mbarrier.arrive.shared::cta.b64 _, [%0];" ::"r"(bar) : "memory");
}
__device__ __forceinline__ void mbar_wait(uint32_t bar, uint32_t parity) {
    asm volatile(
        "{\n"
        ".reg .pred p;\n"
        ".reg .u32 n;\n"
        "mov.u32 n, 0;\n"
        "WAIT_LOOP:\n"
        "mbarrier.try_wait.parity.shared::cta.b64 p, [%0], %1;\n"
        "@p bra WAIT_DONE;\n"
        "add.u32 n, n, 1;\n"
        "setp.lt.u32 p, n, 0x4000000;\n"
        "@p bra WAIT_LOOP;\n"
        "trap;\n"
        "WAIT_DONE:\n"
        "}\n" ::"r"(bar), "r"(parity) : "memory");
}
__device__ __forceinline__ void mbar_wait_cluster(uint32_t bar, uint32_t parity) {
    asm volatile(
        "{\n"
        ".reg .pred p;\n"
        ".reg .u32 n;\n"
        "mov.u32 n, 0;\n"
        "WAIT_LOOP:\n"
        "mbarrier.try_wait.parity.acquire.cluster.shared::cta.b64 p, [%0], %1;\n"
        "@p bra WAIT_DONE;\n"
        "add.u32 n, n, 1;\n"
        "setp.lt.u32 p, n, 0x4000000;\n"
        "@p bra WAIT_LOOP;\n"
        "trap;\n"
        "WAIT_DONE:\n"
        "}\n" ::"r"(bar), "r"(parity) : "memory");
}
__device__ __forceinline__ void tma_tile(uint32_t dst, const CUtensorMap* map, int group, uint32_t bar) {
    asm volatile(
        "cp.async.bulk.tensor.4d.shared::cluster.global.mbarrier::complete_tx::bytes [%0], [%1, {%3, %3, %3, %4}], [%2];"
        ::"r"(dst), "l"(map), "r"(bar), "r"(0), "r"(group) : "memory");
}
__device__ __forceinline__ void ldsm_x4(uint32_t addr, uint32_t (&r)[4]) {
    asm volatile("ldmatrix.sync.aligned.m8n8.x4.shared.b16 {%0,%1,%2,%3}, [%4];"
                 : "=r"(r[0]), "=r"(r[1]), "=r"(r[2]), "=r"(r[3]) : "r"(addr) : "memory");
}
__device__ __forceinline__ void ldsm_x4_t(uint32_t addr, uint32_t (&r)[4]) {
    asm volatile("ldmatrix.sync.aligned.m8n8.x4.trans.shared.b16 {%0,%1,%2,%3}, [%4];"
                 : "=r"(r[0]), "=r"(r[1]), "=r"(r[2]), "=r"(r[3]) : "r"(addr) : "memory");
}
__device__ __forceinline__ void mma_bf16(float (&c)[4], const uint32_t (&a)[4], uint32_t b0, uint32_t b1) {
    asm volatile("mma.sync.aligned.m16n8k16.row.col.f32.bf16.bf16.f32 {%0,%1,%2,%3}, {%4,%5,%6,%7}, {%8,%9}, {%0,%1,%2,%3};"
                 : "+f"(c[0]), "+f"(c[1]), "+f"(c[2]), "+f"(c[3])
                 : "r"(a[0]), "r"(a[1]), "r"(a[2]), "r"(a[3]), "r"(b0), "r"(b1));
}
__device__ __forceinline__ uint32_t pack_bf16(float lo, float hi) {
    uint32_t r;
    asm("cvt.rn.bf16x2.f32 %0, %1, %2;" : "=r"(r) : "f"(hi), "f"(lo));
    return r;
}
__device__ __forceinline__ float bf_lo(uint32_t v) { return __uint_as_float(v << 16); }
__device__ __forceinline__ float bf_hi(uint32_t v) { return __uint_as_float(v & 0xffff0000u); }
__device__ __forceinline__ uint32_t max_bf16x2(uint32_t a, uint32_t b) {
    uint32_t r;
    asm("max.bf16x2 %0, %1, %2;" : "=r"(r) : "r"(a), "r"(b));
    return r;
}
__device__ __forceinline__ float round_bf16(float x) { return bf_lo(pack_bf16(x, 0.f)); }
__device__ __forceinline__ float ex2(float x) {
    float r;
    asm("ex2.approx.ftz.f32 %0, %1;" : "=f"(r) : "f"(x));
    return r;
}
__device__ __forceinline__ uint32_t map_to_cta0(uint32_t addr) {
    uint32_t r;
    asm("mapa.shared::cluster.u32 %0, %1, 0;" : "=r"(r) : "r"(addr));
    return r;
}
__device__ __forceinline__ void st_async_f2(uint32_t addr, float a, float b, uint32_t bar) {
    asm volatile("st.async.weak.shared::cluster.mbarrier::complete_tx::bytes.v2.f32 [%0], {%1, %2}, [%3];"
                 ::"r"(addr), "f"(a), "f"(b), "r"(bar) : "memory");
}
__device__ __forceinline__ void consumer_sync() { asm volatile("bar.sync 1, 256;" ::: "memory"); }
__device__ __forceinline__ float2 lds_f2(uint32_t addr) {
    float2 v;
    asm volatile("ld.shared.v2.f32 {%0,%1}, [%2];" : "=f"(v.x), "=f"(v.y) : "r"(addr) : "memory");
    return v;
}
__device__ __forceinline__ float4 lds_f4(uint32_t addr) {
    float4 v;
    asm volatile("ld.shared.v4.f32 {%0,%1,%2,%3}, [%4];" : "=f"(v.x), "=f"(v.y), "=f"(v.z), "=f"(v.w) : "r"(addr) : "memory");
    return v;
}

#define TS(var)

__global__ void __cluster_dims__(2, 1, 1) __launch_bounds__(kThreads, 1)
tree_attn_kernel(const __nv_bfloat16* __restrict__ q, const __nv_bfloat16* __restrict__ k_tree,
                 const __nv_bfloat16* __restrict__ v_tree, const __nv_bfloat16* __restrict__ tree_mask,
                 __nv_bfloat16* __restrict__ out,
                 const __grid_constant__ CUtensorMap map_k, const __grid_constant__ CUtensorMap map_v) {
    extern __shared__ uint8_t smem_raw[];
    const uint32_t sb = (smem_u32(smem_raw) + 1023u) & ~1023u;
    const uint32_t bar_full = sb + kOffBar;
    const uint32_t bar_empty = bar_full + 8 * kStages;
    const uint32_t bar_stat = bar_empty + 8 * kStages;
    const uint32_t bar_xo = bar_stat + 8;
    const int warp = threadIdx.x >> 5, lane = threadIdx.x & 31;
    const int bh = blockIdx.x >> 1;
    const int rank = blockIdx.x & 1;
    TS(t_start);

    if (warp == 0) {
        const int group0 = blockIdx.x * (kKeysPerCta / 8);
        if (lane == 0) {
#pragma unroll
            for (int s = 0; s < kStages; s++) {
                mbar_init(bar_full + 8 * s, 1);
                mbar_expect_tx(bar_full + 8 * s, kTileBytes);
                tma_tile(sb + kOffRing + s * kTileBytes, &map_k, group0 + s * (kTileKeys / 8), bar_full + 8 * s);
            }
#pragma unroll
            for (int s = 0; s < kStages; s++) mbar_init(bar_empty + 8 * s, kConsumerWarps);
            mbar_init(bar_stat, 1);
            mbar_init(bar_xo, 1);
            mbar_expect_tx(bar_stat, kConsumerWarps * 8);
            mbar_expect_tx(bar_xo, kConsumerWarps * 32 * 8);
            asm volatile("fence.mbarrier_init.release.cluster;" ::: "memory");
        }
        __syncwarp();
        asm volatile("barrier.cluster.arrive.release.aligned;" ::: "memory");
        asm volatile("barrier.cluster.wait.acquire.aligned;" ::: "memory");
        if (lane == 0) {
            int s = 0, ph = 0;
#pragma unroll 1
            for (int i = kStages; i < 2 * kTiles; i++) {
                mbar_wait(bar_empty + 8 * s, ph);
                mbar_expect_tx(bar_full + 8 * s, kTileBytes);
                const bool is_v = i >= kTiles;
                tma_tile(sb + kOffRing + s * kTileBytes, is_v ? &map_v : &map_k,
                         group0 + (i & (kTiles - 1)) * (kTileKeys / 8), bar_full + 8 * s);
                if (++s == kStages) { s = 0; ph ^= 1; }
            }
        }
        return;
    }

    const int w = warp - 1;
    const int g = lane >> 2, t = lane & 3;
    const int mi = lane >> 3, r8 = lane & 7;

    uint32_t qf[8][2];
    {
        const uint32_t* qp = reinterpret_cast<const uint32_t*>(q + (size_t)(bh * kRep + (g & 3)) * kD) + t;
#pragma unroll
        for (int j = 0; j < 8; j++) {
            qf[j][0] = __ldg(qp + j * 8);
            qf[j][1] = __ldg(qp + j * 8 + 4);
        }
    }
    const int h0 = 2 * (t & 1);
    const int d_own = 16 * w + g + 8 * (t >> 1);
    float vt = 0.f;
    if (rank == 0) {
        vt = __bfloat162float(v_tree[bh * kD + d_own]);
        if (w < kRep) {
            const uint2 qa = __ldg(reinterpret_cast<const uint2*>(q + (size_t)(bh * kRep + w) * kD) + lane);
            const uint2 ka = __ldg(reinterpret_cast<const uint2*>(k_tree + (size_t)bh * kD) + lane);
            const float mk = __bfloat162float(tree_mask[bh / kHkv]);
            float s = bf_lo(qa.x) * bf_lo(ka.x);
            s = fmaf(bf_hi(qa.x), bf_hi(ka.x), s);
            s = fmaf(bf_lo(qa.y), bf_lo(ka.y), s);
            s = fmaf(bf_hi(qa.y), bf_hi(ka.y), s);
#pragma unroll
            for (int o = 16; o > 0; o >>= 1) s += __shfl_xor_sync(0xffffffffu, s, o);
            s = round_bf16(round_bf16(s) * kScale);
            s = round_bf16(s + round_bf16(round_bf16(1.0f - mk) * -1000000000.0f));
            if (lane == 0) asm volatile("st.shared.f32 [%0], %1;" ::"r"(sb + kOffTree + 4 * w), "f"(s) : "memory");
        }
    }
    __nv_bfloat16* outp = out + (size_t)(bh * kRep + (g & 3)) * kD + 16 * w + 8 * (g >> 2) + 2 * t;

    asm volatile("barrier.cluster.arrive.release.aligned;" ::: "memory");
    asm volatile("barrier.cluster.wait.acquire.aligned;" ::: "memory");
    TS(t_ready);

    int s = 0, ph = 0;
    uint32_t mx = 0xff80ff80u;
    {
        const uint32_t k_off = sb + kOffRing + (2 * w + (mi & 1)) * 2048 + r8 * 128 + (((mi >> 1) ^ r8) << 4);
        uint32_t s_addr = sb + kOffP + (r8 & 3) * kPitch + (16 * w + 8 * (r8 >> 2)) * 2;
#pragma unroll 1
        for (int i = 0; i < kTiles; i++) {
            mbar_wait(bar_full + 8 * s, ph);
            const uint32_t base = k_off + s * kTileBytes;
            float c0[4] = {0.f, 0.f, 0.f, 0.f}, c1[4] = {0.f, 0.f, 0.f, 0.f};
            uint32_t a[8][4];
#pragma unroll
            for (int j = 0; j < 8; j++) ldsm_x4((base ^ ((j & 3) << 5)) + (j >> 2) * 1024, a[j]);
#pragma unroll
            for (int j = 0; j < 8; j += 2) {
                mma_bf16(c0, a[j], qf[j][0], qf[j][1]);
                mma_bf16(c1, a[j + 1], qf[j + 1][0], qf[j + 1][1]);
            }
            if (lane == 0) mbar_arrive(bar_empty + 8 * s);
            const float x0 = (t < 2) ? c0[0] + c1[0] : c0[2] + c1[2];
            const float x1 = (t < 2) ? c0[1] + c1[1] : c0[3] + c1[3];
            const uint32_t raw = pack_bf16(x0, x1);
            const uint32_t sc = pack_bf16(bf_lo(raw) * kScale, bf_hi(raw) * kScale);
            mx = max_bf16x2(mx, sc);
            asm volatile("stmatrix.sync.aligned.m8n8.x1.trans.shared.b16 [%0], {%1};" ::"r"(s_addr), "r"(sc) : "memory");
            s_addr += kTileKeys * 2;
            if (++s == kStages) { s = 0; ph ^= 1; }
        }
    }
    TS(t_k_done);

    {
#pragma unroll
        for (int o = 2; o < 32; o <<= 1) mx = max_bf16x2(mx, __shfl_xor_sync(0xffffffffu, mx, o));
        if (lane < 2) asm volatile("st.shared.u32 [%0], %1;" ::"r"(sb + kOffWmax + w * 8 + lane * 4), "r"(mx) : "memory");
        consumer_sync();
        const int head = w >> 1;
        uint32_t m2;
        asm volatile("ld.shared.u32 %0, [%1];" : "=r"(m2) : "r"(sb + kOffWmax + r8 * 8 + (head >> 1) * 4) : "memory");
#pragma unroll
        for (int o = 1; o < 8; o <<= 1) m2 = max_bf16x2(m2, __shfl_xor_sync(0xffffffffu, m2, o));
        const float m = (head & 1) ? bf_hi(m2) : bf_lo(m2);
        float sum = 0.f;
        uint32_t p_addr = sb + kOffP + head * kPitch + (w & 1) * kKeysPerCta + lane * 16;
#pragma unroll 2
        for (int i = 0; i < kKeysPerCta / 512; i++) {
            uint32_t v[4];
            asm volatile("ld.shared.v4.u32 {%0,%1,%2,%3}, [%4];" : "=r"(v[0]), "=r"(v[1]), "=r"(v[2]), "=r"(v[3]) : "r"(p_addr) : "memory");
#pragma unroll
            for (int j = 0; j < 4; j++) {
                const float e0 = ex2((bf_lo(v[j]) - m) * kLog2e);
                const float e1 = ex2((bf_hi(v[j]) - m) * kLog2e);
                sum += e0 + e1;
                v[j] = pack_bf16(e0, e1);
            }
            asm volatile("st.shared.v4.u32 [%0], {%1,%2,%3,%4};" ::"r"(p_addr), "r"(v[0]), "r"(v[1]), "r"(v[2]), "r"(v[3]) : "memory");
            p_addr += 512;
        }
#pragma unroll
        for (int o = 16; o > 0; o >>= 1) sum += __shfl_xor_sync(0xffffffffu, sum, o);
        if (lane == 0) {
            if (rank == 0) asm volatile("st.shared.v2.f32 [%0], {%1,%2};" ::"r"(sb + kOffStatL + w * 8), "f"(m), "f"(sum) : "memory");
            else st_async_f2(map_to_cta0(sb + kOffStatR + w * 8), m, sum, map_to_cta0(bar_stat));
        }
        consumer_sync();
    }
    TS(t_mid_done);

    float o0[4] = {0.f, 0.f, 0.f, 0.f}, o1[4] = {0.f, 0.f, 0.f, 0.f};
    float f_loc0 = 0.f, f_loc1 = 0.f, f_rem0 = 0.f, f_rem1 = 0.f, tr0 = 0.f, tr1 = 0.f;
    {
        const int chunk = 2 * w + (mi & 1);
        const uint32_t v_off = sb + kOffRing + (mi >> 1) * 2048 + (chunk >> 3) * 1024 + r8 * 128 + (((chunk & 7) ^ r8) << 4);
        uint32_t p_addr = sb + kOffP + (r8 & 3) * kPitch + mi * 16;
#pragma unroll 1
        for (int i = 0; i < kTiles; i++) {
            uint32_t b[4][4];
#pragma unroll
            for (int u = 0; u < 4; u++) ldsm_x4(p_addr + u * 64, b[u]);
            p_addr += kTileKeys * 2;
            if (i == 8 && rank == 0) {
                mbar_wait_cluster(bar_stat, 0);
                const float4 la = lds_f4(sb + kOffStatL + h0 * 16), lb = lds_f4(sb + kOffStatL + h0 * 16 + 16);
                const float4 ra = lds_f4(sb + kOffStatR + h0 * 16), rb = lds_f4(sb + kOffStatR + h0 * 16 + 16);
                const float2 st = lds_f2(sb + kOffTree + h0 * 4);
                {
                    const float m = fmaxf(fmaxf(la.x, ra.x), st.x);
                    const float el = ex2((la.x - m) * kLog2e), er = ex2((ra.x - m) * kLog2e), et = ex2((st.x - m) * kLog2e);
                    const float inv = 1.0f / (el * (la.y + la.w) + er * (ra.y + ra.w) + et);
                    f_loc0 = el * inv; f_rem0 = er * inv; tr0 = et * inv * vt;
                }
                {
                    const float m = fmaxf(fmaxf(lb.x, rb.x), st.y);
                    const float el = ex2((lb.x - m) * kLog2e), er = ex2((rb.x - m) * kLog2e), et = ex2((st.y - m) * kLog2e);
                    const float inv = 1.0f / (el * (lb.y + lb.w) + er * (rb.y + rb.w) + et);
                    f_loc1 = el * inv; f_rem1 = er * inv; tr1 = et * inv * vt;
                }
            }
            mbar_wait(bar_full + 8 * s, ph);
            const uint32_t base = v_off + s * kTileBytes;
            uint32_t a[8][4];
#pragma unroll
            for (int j = 0; j < 8; j++) ldsm_x4_t(base + j * 4096, a[j]);
#pragma unroll
            for (int u = 0; u < 4; u++) {
                mma_bf16(o0, a[2 * u], b[u][0], b[u][1]);
                mma_bf16(o1, a[2 * u + 1], b[u][2], b[u][3]);
            }
            if (lane == 0) mbar_arrive(bar_empty + 8 * s);
            if (++s == kStages) { s = 0; ph ^= 1; }
        }
    }
    TS(t_v_done);

    const float x0 = (t < 2) ? o0[0] + o1[0] : o0[2] + o1[2];
    const float x1 = (t < 2) ? o0[1] + o1[1] : o0[3] + o1[3];
    const uint32_t x_addr = sb + kOffX + (w * 32 + lane) * 8;
    if (rank != 0) {
        st_async_f2(map_to_cta0(x_addr), x0, x1, map_to_cta0(bar_xo));
    } else {
        const float y0 = fmaf(x0, f_loc0, tr0), y1 = fmaf(x1, f_loc1, tr1);
        mbar_wait_cluster(bar_xo, 0);
        const float2 rem = lds_f2(x_addr);
        const uint32_t pk = pack_bf16(fmaf(rem.x, f_rem0, y0), fmaf(rem.y, f_rem1, y1));
        uint32_t tr;
        asm volatile("movmatrix.sync.aligned.m8n8.trans.b16 %0, %1;" : "=r"(tr) : "r"(pk));
        *reinterpret_cast<uint32_t*>(outp) = tr;
    }
}

typedef CUresult (*EncodeTiledFn)(CUtensorMap*, CUtensorMapDataType, cuuint32_t, void*, const cuuint64_t*,
                                  const cuuint64_t*, const cuuint32_t*, const cuuint32_t*, CUtensorMapInterleave,
                                  CUtensorMapSwizzle, CUtensorMapL2promotion, CUtensorMapFloatOOBfill);

void encode_cache_map(EncodeTiledFn enc, CUtensorMap* map, const void* base) {
    const cuuint64_t dims[4] = {64, 8, 2, (cuuint64_t)kB * kHkv * kC / 8};
    const cuuint64_t strides[3] = {256, 128, 2048};
    const cuuint32_t box[4] = {64, 8, 2, kTileKeys / 8};
    const cuuint32_t estr[4] = {1, 1, 1, 1};
    enc(map, CU_TENSOR_MAP_DATA_TYPE_BFLOAT16, 4, const_cast<void*>(base), dims, strides, box, estr,
        CU_TENSOR_MAP_INTERLEAVE_NONE, CU_TENSOR_MAP_SWIZZLE_128B, CU_TENSOR_MAP_L2_PROMOTION_NONE,
        CU_TENSOR_MAP_FLOAT_OOB_FILL_NONE);
}

}

extern "C" void kernel_launch(void* const* d_in, const int* in_sizes, int n_in, void* d_out, int out_size) {
    (void)in_sizes; (void)n_in; (void)out_size;
    static EncodeTiledFn enc = nullptr;
    if (!enc) {
        void* fn = nullptr;
        cudaDriverEntryPointQueryResult qr;
        cudaGetDriverEntryPoint("cuTensorMapEncodeTiled", &fn, cudaEnableDefault, &qr);
        enc = (EncodeTiledFn)fn;
        cudaFuncSetAttribute(tree_attn_kernel, cudaFuncAttributeMaxDynamicSharedMemorySize, kSmemBytes);
    }
    CUtensorMap map_k, map_v;
    encode_cache_map(enc, &map_k, d_in[1]);
    encode_cache_map(enc, &map_v, d_in[2]);
    tree_attn_kernel<<<kB * kHkv * 2, kThreads, kSmemBytes>>>(
        (const __nv_bfloat16*)d_in[0], (const __nv_bfloat16*)d_in[3], (const __nv_bfloat16*)d_in[4],
        (const __nv_bfloat16*)d_in[5], (__nv_bfloat16*)d_out, map_k, map_v);
}
```

```cpp
#include <cuda_runtime.h>
#include <cuda_bf16.h>
#include <cuda.h>
#include <stdint.h>

namespace {

constexpr int kB = 8, kHq = 32, kHkv = 8, kC = 8192, kD = 128;
constexpr int kRep = kHq / kHkv;
constexpr int kHeads = kB * kHkv;
constexpr int kCtas = 2 * kHeads;
constexpr int kStageBytes = 128 * kD * 2;
#define STAGES 4
#define PF 16384
#define NPRE 2
#define DELTA 184
#define PSTART 8
#define MSLEEP 100
#define PSLEEP 20
#define NHALF 0
constexpr int kStages = STAGES;
constexpr int kPassStages = 32;
constexpr int kTotal = 2 * kPassStages;
constexpr int kPre = NPRE;
constexpr int kHalf = NHALF;
constexpr int kGroupsPerCta = kC / 2 / 8;
constexpr int kConsumerWarps = 8;
constexpr int kThreads = 32 * (kConsumerWarps + 2);
constexpr int kPitch = kPassStages * 128 * 2 + 16;
constexpr int kPaceTicks = kCtas * (kTotal - kStages);

constexpr int kOffRing = 0;
constexpr int kOffP = kOffRing + kStages * kStageBytes;
constexpr int kOffQ = kOffP + kRep * kPitch;
constexpr int kOffX = kOffQ + kRep * kD * 2;
constexpr int kOffWmax = kOffX + 2048;
constexpr int kOffStatL = kOffWmax + 64;
constexpr int kOffStatR = kOffStatL + 64;
constexpr int kOffTree = kOffStatR + 64;
constexpr int kOffKt = kOffTree + 16;
constexpr int kOffVt = kOffKt + kD * 2;
constexpr int kOffMask = kOffVt + kD * 2;
constexpr int kOffPace = kOffMask + 16;
constexpr int kOffBar = kOffPace + 16;
constexpr int kSmemUsed = kOffBar + 8 * (2 * kStages + 3 + kHalf);
constexpr int kSmemBytes = kSmemUsed + 1024;
static_assert(kSmemBytes <= 232448, "shared memory");

constexpr float kScale = 0.08838834764831845f;
constexpr float kLog2e = 1.4426950408889634f;
constexpr uint32_t kNegInf2 = 0xff80ff80u;
constexpr uint64_t kEvictFirst = 0x12F0000000000000ull;

__device__ unsigned int g_pace[32];

__device__ __forceinline__ uint32_t smem_u32(const void* p) { return (uint32_t)__cvta_generic_to_shared(p); }
__device__ __forceinline__ void mbar_init(uint32_t bar, int cnt) {
    asm volatile("mbarrier.init.shared::cta.b64 [%0], %1;" ::"r"(bar), "r"(cnt) : "memory");
}
__device__ __forceinline__ void mbar_expect_tx(uint32_t bar, uint32_t bytes) {
    asm volatile("mbarrier.arrive.expect_tx.shared::cta.b64 _, [%0], %1;" ::"r"(bar), "r"(bytes) : "memory");
}
__device__ __forceinline__ void mbar_arrive(uint32_t bar) {
    asm volatile("mbarrier.arrive.shared::cta.b64 _, [%0];" ::"r"(bar) : "memory");
}
__device__ __forceinline__ void mbar_wait(uint32_t bar, uint32_t parity) {
    asm volatile(
        "{\n"
        ".reg .pred p;\n"
        ".reg .u32 n;\n"
        "mov.u32 n, 0;\n"
        "WAIT_LOOP:\n"
        "mbarrier.try_wait.parity.shared::cta.b64 p, [%0], %1;\n"
        "@p bra WAIT_DONE;\n"
        "add.u32 n, n, 1;\n"
        "setp.lt.u32 p, n, 0x1000000;\n"
        "@p bra WAIT_LOOP;\n"
        "trap;\n"
        "WAIT_DONE:\n"
        "}\n" ::"r"(bar), "r"(parity) : "memory");
}
__device__ __forceinline__ void tma_box(uint32_t dst, const CUtensorMap* map, int group, int tensor, uint32_t bar) {
    asm volatile(
        "cp.async.bulk.tensor.5d.shared::cluster.global.mbarrier::complete_tx::bytes.L2::cache_hint [%0], [%1, {%3, %3, %3, %4, %5}], [%2], %6;"
        ::"r"(dst), "l"(map), "r"(bar), "r"(0), "r"(group), "r"(tensor), "l"(kEvictFirst) : "memory");
}
__device__ __forceinline__ void bulk_copy(uint32_t dst, const void* src, uint32_t bytes, uint32_t bar) {
    asm volatile("cp.async.bulk.shared::cluster.global.mbarrier::complete_tx::bytes [%0], [%1], %2, [%3];"
                 ::"r"(dst), "l"(src), "r"(bytes), "r"(bar) : "memory");
}
__device__ __forceinline__ bool elect_one() {
    uint32_t p;
    asm volatile("{\n.reg .pred p;\nelect.sync _|p, 0xffffffff;\nselp.u32 %0, 1, 0, p;\n}\n" : "=r"(p));
    return p != 0;
}
template <typename T> __device__ __forceinline__ void pin32(T& v) { asm volatile("" : "+r"(v)); }
template <typename T> __device__ __forceinline__ void pin64(T& v) { asm volatile("" : "+l"(v)); }
__device__ __forceinline__ void ldsm_x4(uint32_t addr, uint32_t (&r)[4]) {
    asm volatile("ldmatrix.sync.aligned.m8n8.x4.shared.b16 {%0,%1,%2,%3}, [%4];"
                 : "=r"(r[0]), "=r"(r[1]), "=r"(r[2]), "=r"(r[3]) : "r"(addr) : "memory");
}
__device__ __forceinline__ void ldsm_x4_t(uint32_t addr, uint32_t (&r)[4]) {
    asm volatile("ldmatrix.sync.aligned.m8n8.x4.trans.shared.b16 {%0,%1,%2,%3}, [%4];"
                 : "=r"(r[0]), "=r"(r[1]), "=r"(r[2]), "=r"(r[3]) : "r"(addr) : "memory");
}
__device__ __forceinline__ void stsm_x1_t(uint32_t addr, uint32_t v) {
    asm volatile("stmatrix.sync.aligned.m8n8.x1.trans.shared.b16 [%0], {%1};" ::"r"(addr), "r"(v) : "memory");
}
__device__ __forceinline__ void mma_bf16(float (&c)[4], const uint32_t (&a)[4], uint32_t b0, uint32_t b1) {
    asm volatile("mma.sync.aligned.m16n8k16.row.col.f32.bf16.bf16.f32 {%0,%1,%2,%3}, {%4,%5,%6,%7}, {%8,%9}, {%0,%1,%2,%3};"
                 : "+f"(c[0]), "+f"(c[1]), "+f"(c[2]), "+f"(c[3])
                 : "r"(a[0]), "r"(a[1]), "r"(a[2]), "r"(a[3]), "r"(b0), "r"(b1));
}
__device__ __forceinline__ uint32_t pack_bf16(float lo, float hi) {
    uint32_t r;
    asm("cvt.rn.bf16x2.f32 %0, %1, %2;" : "=r"(r) : "f"(hi), "f"(lo));
    return r;
}
__device__ __forceinline__ float bf_lo(uint32_t v) { return __uint_as_float(v << 16); }
__device__ __forceinline__ float bf_hi(uint32_t v) { return __uint_as_float(v & 0xffff0000u); }
__device__ __forceinline__ uint32_t max_bf16x2(uint32_t a, uint32_t b) {
    uint32_t r;
    asm("max.bf16x2 %0, %1, %2;" : "=r"(r) : "r"(a), "r"(b));
    return r;
}
__device__ __forceinline__ float round_bf16(float x) { return bf_lo(pack_bf16(x, 0.f)); }
__device__ __forceinline__ float exp_diff(float x, float m) {
    float r;
    asm("ex2.approx.ftz.f32 %0, %1;" : "=f"(r) : "f"((x - m) * kLog2e));
    return r;
}
__device__ __forceinline__ uint32_t map_to_cta0(uint32_t addr) {
    uint32_t r;
    asm("mapa.shared::cluster.u32 %0, %1, 0;" : "=r"(r) : "r"(addr));
    return r;
}
__device__ __forceinline__ void st_async_f2(uint32_t addr, float a, float b, uint32_t bar) {
    asm volatile("st.async.weak.shared::cluster.mbarrier::complete_tx::bytes.v2.f32 [%0], {%1, %2}, [%3];"
                 ::"r"(addr), "f"(a), "f"(b), "r"(bar) : "memory");
}
__device__ __forceinline__ void consumer_sync() { asm volatile("bar.sync 1, 256;" ::: "memory"); }
__device__ __forceinline__ float2 lds_f2(uint32_t addr) {
    float2 v;
    asm volatile("ld.shared.v2.f32 {%0,%1}, [%2];" : "=f"(v.x), "=f"(v.y) : "r"(addr) : "memory");
    return v;
}
__device__ __forceinline__ float4 lds_f4(uint32_t addr) {
    float4 v;
    asm volatile("ld.shared.v4.f32 {%0,%1,%2,%3}, [%4];" : "=f"(v.x), "=f"(v.y), "=f"(v.z), "=f"(v.w) : "r"(addr) : "memory");
    return v;
}
__device__ __forceinline__ void lds_u4(uint32_t addr, uint32_t (&v)[4]) {
    asm volatile("ld.shared.v4.u32 {%0,%1,%2,%3}, [%4];" : "=r"(v[0]), "=r"(v[1]), "=r"(v[2]), "=r"(v[3]) : "r"(addr) : "memory");
}
__device__ __forceinline__ void sts_u4(uint32_t addr, const uint32_t (&v)[4]) {
    asm volatile("st.shared.v4.u32 [%0], {%1,%2,%3,%4};" ::"r"(addr), "r"(v[0]), "r"(v[1]), "r"(v[2]), "r"(v[3]) : "memory");
}
__device__ __forceinline__ void sts_f2(uint32_t addr, float a, float b) {
    asm volatile("st.shared.v2.f32 [%0], {%1,%2};" ::"r"(addr), "f"(a), "f"(b) : "memory");
}
__device__ __forceinline__ int lds_volatile(uint32_t addr) {
    int v;
    asm volatile("ld.volatile.shared.s32 %0, [%1];" : "=r"(v) : "r"(addr) : "memory");
    return v;
}
__device__ __forceinline__ void sts_volatile(uint32_t addr, int v) {
    asm volatile("st.volatile.shared.s32 [%0], %1;" ::"r"(addr), "r"(v) : "memory");
}

#define TS(var)

struct alignas(64) Params {
    const char* k_raw;
    const __nv_bfloat16 *q, *k_tree, *v_tree, *tree_mask;
    __nv_bfloat16* out;
    unsigned int* pace;
    int k_idx;
    CUtensorMap stage;
};

__global__ void __cluster_dims__(2, 1, 1) __launch_bounds__(kThreads, 1)
tree_attn_kernel(const __grid_constant__ Params prm) {
    TS(t_start);
    if (PF > 0 && threadIdx.x == 0)
        asm volatile("cp.async.bulk.prefetch.L2.global.L2::cache_hint [%0], %1, %2;"
                     ::"l"(prm.k_raw + (size_t)blockIdx.x * (kGroupsPerCta * 2048)), "r"(PF), "l"(kEvictFirst) : "memory");

    extern __shared__ uint8_t smem_raw[];
    const uint32_t sb = (smem_u32(smem_raw) + 1023u) & ~1023u;
    const uint32_t ring = sb + kOffRing;
    const uint32_t bar_full = sb + kOffBar;
    const uint32_t bar_empty = bar_full + 8 * kStages;
    const uint32_t bar_stat = bar_empty + 8 * kStages;
    const uint32_t bar_q = bar_stat + 8;
    const uint32_t bar_xo = bar_q + 8;
    const uint32_t bar_half = bar_xo + 8;
    const int warp = threadIdx.x >> 5, lane = threadIdx.x & 31;
    const int bh = blockIdx.x >> 1;
    const int rank = blockIdx.x & 1;
    const int group0 = blockIdx.x * kGroupsPerCta;
    const int ik = prm.k_idx;

    if (warp == 0) {
        if (elect_one()) {
            mbar_init(bar_full, 1);
            mbar_expect_tx(bar_full, kStageBytes);
            tma_box(ring, &prm.stage, group0, ik, bar_full);
#pragma unroll
            for (int s = 1; s < kStages; s++) mbar_init(bar_full + 8 * s, 1);
            mbar_init(bar_q, 1);
            mbar_expect_tx(bar_q, kRep * kD * 2 + (rank == 0 ? 2 * kD * 2 + 16 : 0));
            bulk_copy(sb + kOffQ, prm.q + (size_t)bh * kRep * kD, kRep * kD * 2, bar_q);
            mbar_expect_tx(bar_full + 8, kStageBytes);
            tma_box(ring + kStageBytes, &prm.stage, group0 + 16, ik, bar_full + 8);
            if (rank == 0) {
                bulk_copy(sb + kOffKt, prm.k_tree + (size_t)bh * kD, kD * 2, bar_q);
                bulk_copy(sb + kOffVt, prm.v_tree + (size_t)bh * kD, kD * 2, bar_q);
                bulk_copy(sb + kOffMask, prm.tree_mask, 16, bar_q);
            }
#pragma unroll
            for (int s = 2; s < kStages; s++) {
                mbar_expect_tx(bar_full + 8 * s, kStageBytes);
                tma_box(ring + s * kStageBytes, &prm.stage, group0 + s * 16, ik, bar_full + 8 * s);
            }
#pragma unroll
            for (int s = 0; s < kStages; s++) mbar_init(bar_empty + 8 * s, kConsumerWarps);
            mbar_init(bar_stat, 1);
#pragma unroll
            for (int u = 0; u < 1 + kHalf; u++) mbar_init(bar_xo + 8 * u, 1);
            mbar_expect_tx(bar_stat, kConsumerWarps * 8);
            mbar_expect_tx(bar_xo, kConsumerWarps * 32 * 8);
            sts_volatile(sb + kOffPace, PSTART * kCtas);
            sts_volatile(sb + kOffPace + 4, 0);
            asm volatile("fence.mbarrier_init.release.cluster;" ::: "memory");
        }
        __syncwarp();
    }
    __syncthreads();
    asm volatile("barrier.cluster.arrive.relaxed.aligned;" ::: "memory");

    if (warp == 0) {
        if (elect_one()) {
            unsigned int* pace = prm.pace;
            int s = 0, ph = 0, patience = 400;
#pragma unroll 1
            for (int i = kStages; i < kTotal; i++) {
                mbar_wait(bar_empty + 8 * s, ph);
                while (i * kCtas > lds_volatile(sb + kOffPace) && patience > 0) { patience--; __nanosleep(PSLEEP); }
                if (patience > 0) patience = 400;
                const uint32_t dst = ring + s * kStageBytes;
                const int grp = group0 + (i & (kPassStages - 1)) * 16;
                {
                    mbar_expect_tx(bar_full + 8 * s, kStageBytes);
                    tma_box(dst, &prm.stage, grp, ik ^ (i >> 5), bar_full + 8 * s);
                }
                asm volatile("red.relaxed.gpu.global.inc.u32 [%0], %1;" ::"l"(pace), "r"(kPaceTicks - 1) : "memory");
                if (++s == kStages) { s = 0; ph ^= 1; }
            }
            sts_volatile(sb + kOffPace + 4, 1);
        }
        __syncwarp();
        asm volatile("barrier.cluster.wait.aligned;" ::: "memory");
        return;
    }
    if (warp == 1) {
        asm volatile("barrier.cluster.wait.aligned;" ::: "memory");
        if (elect_one()) {
            const unsigned int* pace = prm.pace;
            int limit = PSTART * kCtas;
#pragma unroll 1
            for (int n = 0; n < (1 << 20) && lds_volatile(sb + kOffPace + 4) == 0; n++) {
                unsigned int ticks;
                asm volatile("ld.relaxed.gpu.global.u32 %0, [%1];" : "=r"(ticks) : "l"(pace) : "memory");
                const int v = (kStages - 1) * kCtas + DELTA + (int)ticks;
                if (v > limit) { limit = v; sts_volatile(sb + kOffPace, v); }
                __nanosleep(MSLEEP);
            }
        }
        return;
    }

    const int w = warp - 2;
    const int g = lane >> 2, t = lane & 3;
    const int mi = lane >> 3, r8 = lane & 7;
    const bool low_half = t < 2;
    uint32_t k_off = ring + (2 * w + (mi & 1)) * 2048 + r8 * 128 + (((mi >> 1) ^ r8) << 4);
    const int chunk = 2 * w + (mi & 1);
    uint32_t v_off = ring + (mi >> 1) * 2048 + (chunk >> 3) * 1024 + r8 * 128 + (((chunk & 7) ^ r8) << 4);
    uint32_t s_addr = sb + kOffP + (r8 & 3) * kPitch + (16 * w + 8 * (r8 >> 2)) * 2;
    uint32_t p_addr = sb + kOffP + (r8 & 3) * kPitch + mi * 16;
    pin32(k_off);
    pin32(v_off);
    const int h0 = 2 * (t & 1);
    const int d_own = 16 * w + g + 8 * (t >> 1);
    __nv_bfloat16* outp = prm.out + (size_t)(bh * kRep + (g & 3)) * kD + 16 * w + 8 * (g >> 2) + 2 * t;
    pin64(outp);
    uint32_t x_addr = sb + kOffX + (w * 32 + lane) * 8;
    uint32_t x_bar = bar_xo;
    if (rank != 0) { x_addr = map_to_cta0(x_addr); x_bar = map_to_cta0(x_bar); }
    pin32(x_addr);
    pin32(x_bar);

    asm volatile("barrier.cluster.wait.aligned;" ::: "memory");
    mbar_wait(bar_q, 0);
    uint32_t qf[4][4];
#pragma unroll
    for (int j = 0; j < 4; j++) ldsm_x4(sb + kOffQ + (r8 & 3) * (kD * 2) + mi * 16 + j * 64, qf[j]);
    if (rank == 0 && w < kRep) {
        uint2 qa, ka;
        uint16_t mk16;
        asm volatile("ld.shared.v2.u32 {%0,%1}, [%2];" : "=r"(qa.x), "=r"(qa.y) : "r"(sb + kOffQ + w * (kD * 2) + lane * 8) : "memory");
        asm volatile("ld.shared.v2.u32 {%0,%1}, [%2];" : "=r"(ka.x), "=r"(ka.y) : "r"(sb + kOffKt + lane * 8) : "memory");
        asm volatile("ld.shared.u16 %0, [%1];" : "=h"(mk16) : "r"(sb + kOffMask + (bh / kHkv) * 2) : "memory");
        float sc = bf_lo(qa.x) * bf_lo(ka.x);
        sc = fmaf(bf_hi(qa.x), bf_hi(ka.x), sc);
        sc = fmaf(bf_lo(qa.y), bf_lo(ka.y), sc);
        sc = fmaf(bf_hi(qa.y), bf_hi(ka.y), sc);
#pragma unroll
        for (int o = 16; o > 0; o >>= 1) sc += __shfl_xor_sync(0xffffffffu, sc, o);
        sc = round_bf16(round_bf16(sc) * kScale);
        sc = round_bf16(sc + round_bf16(round_bf16(1.0f - bf_lo(mk16)) * -1000000000.0f));
        if (lane == 0) asm volatile("st.shared.f32 [%0], %1;" ::"r"(sb + kOffTree + 4 * w), "f"(sc) : "memory");
    }
    TS(t_ready);

    int s = 0, ph = 0;
    uint32_t mx = kNegInf2;
#pragma unroll 1
    for (int i = 0; i < kPassStages; i++) {
        uint32_t base = k_off + s * kStageBytes;
        pin32(base);
        mbar_wait(bar_full + 8 * s, ph);
        float c0[4] = {0.f, 0.f, 0.f, 0.f}, c1[4] = {0.f, 0.f, 0.f, 0.f};
        uint32_t a[8][4];
#pragma unroll
        for (int j = 0; j < 8; j++) ldsm_x4((base ^ ((j & 3) << 5)) + (j >> 2) * 1024, a[j]);
#pragma unroll
        for (int j = 0; j < 8; j += 2) {
            mma_bf16(c0, a[j], qf[j >> 1][0], qf[j >> 1][1]);
            mma_bf16(c1, a[j + 1], qf[j >> 1][2], qf[j >> 1][3]);
        }
        if (lane == 0) mbar_arrive(bar_empty + 8 * s);
        const float x0 = low_half ? c0[0] + c1[0] : c0[2] + c1[2];
        const float x1 = low_half ? c0[1] + c1[1] : c0[3] + c1[3];
        const uint32_t raw = pack_bf16(x0, x1);
        const uint32_t sc = pack_bf16(bf_lo(raw) * kScale, bf_hi(raw) * kScale);
        mx = max_bf16x2(mx, sc);
        stsm_x1_t(s_addr, sc);
        s_addr += 256;
        if (++s == kStages) { s = 0; ph ^= 1; }
    }
    TS(t_k_done);

    {
#pragma unroll
        for (int o = 2; o < 32; o <<= 1) mx = max_bf16x2(mx, __shfl_xor_sync(0xffffffffu, mx, o));
        if (lane < 2) asm volatile("st.shared.u32 [%0], %1;" ::"r"(sb + kOffWmax + w * 8 + lane * 4), "r"(mx) : "memory");
        consumer_sync();
        const int head = w >> 1;
        uint32_t m2;
        asm volatile("ld.shared.u32 %0, [%1];" : "=r"(m2) : "r"(sb + kOffWmax + r8 * 8 + (head >> 1) * 4) : "memory");
#pragma unroll
        for (int o = 1; o < 8; o <<= 1) m2 = max_bf16x2(m2, __shfl_xor_sync(0xffffffffu, m2, o));
        const float m = (head & 1) ? bf_hi(m2) : bf_lo(m2);
        float sum = 0.f;
        uint32_t addr = sb + kOffP + head * kPitch + (w & 1) * (kPassStages * 128) + lane * 16;
#pragma unroll 2
        for (int i = 0; i < kPassStages / 4; i++) {
            uint32_t v[4];
            lds_u4(addr, v);
#pragma unroll
            for (int j = 0; j < 4; j++) {
                const float e0 = exp_diff(bf_lo(v[j]), m), e1 = exp_diff(bf_hi(v[j]), m);
                sum += e0 + e1;
                v[j] = pack_bf16(e0, e1);
            }
            sts_u4(addr, v);
            addr += 512;
        }
#pragma unroll
        for (int o = 16; o > 0; o >>= 1) sum += __shfl_xor_sync(0xffffffffu, sum, o);
        if (lane == 0) {
            if (rank == 0) sts_f2(sb + kOffStatL + w * 8, m, sum);
            else st_async_f2(map_to_cta0(sb + kOffStatR + w * 8), m, sum, map_to_cta0(bar_stat));
        }
        consumer_sync();
    }
    TS(t_mid_done);

    float o0[4] = {0.f, 0.f, 0.f, 0.f}, o1[4] = {0.f, 0.f, 0.f, 0.f};
    float f_loc0 = 0.f, f_loc1 = 0.f, f_rem0 = 0.f, f_rem1 = 0.f, tr0 = 0.f, tr1 = 0.f;
#pragma unroll 1
    for (int i = 0; i < kPassStages - kPre; i++) {
        uint32_t b[4][4];
#pragma unroll
        for (int u = 0; u < 4; u++) ldsm_x4(p_addr + u * 64, b[u]);
        p_addr += 256;
        if (i == 8 && rank == 0) {
            mbar_wait(bar_stat, 0);
            const float4 la = lds_f4(sb + kOffStatL + h0 * 16), lb = lds_f4(sb + kOffStatL + h0 * 16 + 16);
            const float4 ra = lds_f4(sb + kOffStatR + h0 * 16), rb = lds_f4(sb + kOffStatR + h0 * 16 + 16);
            const float2 st = lds_f2(sb + kOffTree + h0 * 4);
            uint16_t vt16;
            asm volatile("ld.shared.u16 %0, [%1];" : "=h"(vt16) : "r"(sb + kOffVt + d_own * 2) : "memory");
            const float vt = bf_lo(vt16);
            {
                const float m = fmaxf(fmaxf(la.x, ra.x), st.x);
                const float el = exp_diff(la.x, m), er = exp_diff(ra.x, m), et = exp_diff(st.x, m);
                const float inv = __frcp_rn(el * (la.y + la.w) + er * (ra.y + ra.w) + et);
                f_loc0 = el * inv; f_rem0 = er * inv; tr0 = et * inv * vt;
            }
            {
                const float m = fmaxf(fmaxf(lb.x, rb.x), st.y);
                const float el = exp_diff(lb.x, m), er = exp_diff(rb.x, m), et = exp_diff(st.y, m);
                const float inv = __frcp_rn(el * (lb.y + lb.w) + er * (rb.y + rb.w) + et);
                f_loc1 = el * inv; f_rem1 = er * inv; tr1 = et * inv * vt;
            }
        }
        uint32_t base = v_off + s * kStageBytes;
        pin32(base);
        mbar_wait(bar_full + 8 * s, ph);
        uint32_t a[8][4];
#pragma unroll
        for (int j = 0; j < 8; j++) ldsm_x4_t(base + j * 4096, a[j]);
#pragma unroll
        for (int u = 0; u < 4; u++) {
            mma_bf16(o0, a[2 * u], b[u][0], b[u][1]);
            mma_bf16(o1, a[2 * u + 1], b[u][2], b[u][3]);
        }
        if (lane == 0) mbar_arrive(bar_empty + 8 * s);
        if (++s == kStages) { s = 0; ph ^= 1; }
    }
    {
        uint32_t b[4 * kPre + 1][4];
#pragma unroll
        for (int u = 0; u < 4 * kPre; u++) ldsm_x4(p_addr + u * 64, b[u]);
#pragma unroll
        for (int e = 0; e < kPre; e++) {
            const int i = kTotal - kPre + e;
            const uint32_t base = v_off + (i % kStages) * kStageBytes;
            mbar_wait(bar_full + 8 * (i % kStages), (i / kStages) & 1);
            uint32_t a[8][4];
#pragma unroll
            for (int j = 0; j < 4; j++) ldsm_x4_t(base + j * 4096, a[j]);
            if (i >= kTotal - kHalf) {
#pragma unroll
                for (int u = 0; u < 2; u++) {
                    mma_bf16(o0, a[2 * u], b[4 * e + u][0], b[4 * e + u][1]);
                    mma_bf16(o1, a[2 * u + 1], b[4 * e + u][2], b[4 * e + u][3]);
                }
                mbar_wait(bar_half + 8 * (i - (kTotal - kHalf)), 0);
            }
#pragma unroll
            for (int j = 4; j < 8; j++) ldsm_x4_t(base + j * 4096, a[j]);
#pragma unroll
            for (int u = (i >= kTotal - kHalf) ? 2 : 0; u < 4; u++) {
                mma_bf16(o0, a[2 * u], b[4 * e + u][0], b[4 * e + u][1]);
                mma_bf16(o1, a[2 * u + 1], b[4 * e + u][2], b[4 * e + u][3]);
            }
            if (i + kStages < kTotal && lane == 0) mbar_arrive(bar_empty + 8 * (i % kStages));
        }
    }
    TS(t_v_done);

    const float x0 = low_half ? o0[0] + o1[0] : o0[2] + o1[2];
    const float x1 = low_half ? o0[1] + o1[1] : o0[3] + o1[3];
    if (rank != 0) {
        st_async_f2(x_addr, x0, x1, x_bar);
    } else {
        const float y0 = fmaf(x0, f_loc0, tr0), y1 = fmaf(x1, f_loc1, tr1);
        mbar_wait(x_bar, 0);
        const float2 rem = lds_f2(x_addr);
        const uint32_t pk = pack_bf16(fmaf(rem.x, f_rem0, y0), fmaf(rem.y, f_rem1, y1));
        uint32_t tr;
        asm volatile("movmatrix.sync.aligned.m8n8.trans.b16 %0, %1;" : "=r"(tr) : "r"(pk));
        asm volatile("st.global.u32 [%0], %1;" ::"l"(outp), "r"(tr) : "memory");
    }
}

typedef CUresult (*EncodeTiledFn)(CUtensorMap*, CUtensorMapDataType, cuuint32_t, void*, const cuuint64_t*,
                                  const cuuint64_t*, const cuuint32_t*, const cuuint32_t*, CUtensorMapInterleave,
                                  CUtensorMapSwizzle, CUtensorMapL2promotion, CUtensorMapFloatOOBfill);

void encode_cache_map(EncodeTiledFn enc, CUtensorMap* map, const char* lo, const char* hi, int groups) {
    const cuuint64_t dims[5] = {64, 8, 2, (cuuint64_t)kHeads * kC / 8, 2};
    const cuuint64_t strides[4] = {256, 128, 2048, (cuuint64_t)(hi - lo)};
    const cuuint32_t box[5] = {64, 8, 2, (cuuint32_t)groups, 1};
    const cuuint32_t estr[5] = {1, 1, 1, 1, 1};
    enc(map, CU_TENSOR_MAP_DATA_TYPE_BFLOAT16, 5, const_cast<char*>(lo), dims, strides, box, estr,
        CU_TENSOR_MAP_INTERLEAVE_NONE, CU_TENSOR_MAP_SWIZZLE_128B, CU_TENSOR_MAP_L2_PROMOTION_NONE,
        CU_TENSOR_MAP_FLOAT_OOB_FILL_NONE);
}

}

extern "C" void kernel_launch(void* const* d_in, const int* in_sizes, int n_in, void* d_out, int out_size) {
    (void)in_sizes; (void)n_in; (void)out_size;
    static EncodeTiledFn enc = nullptr;
    static void* pace = nullptr;
    if (!enc) {
        void* fn = nullptr;
        cudaDriverEntryPointQueryResult qr;
        cudaGetDriverEntryPoint("cuTensorMapEncodeTiled", &fn, cudaEnableDefault, &qr);
        enc = (EncodeTiledFn)fn;
        cudaGetSymbolAddress(&pace, g_pace);
        cudaFuncSetAttribute(tree_attn_kernel, cudaFuncAttributeMaxDynamicSharedMemorySize, kSmemBytes);
    }
    const char* kc = (const char*)d_in[1];
    const char* vc = (const char*)d_in[2];
    Params prm;
    prm.k_raw = kc;
    prm.q = (const __nv_bfloat16*)d_in[0];
    prm.k_tree = (const __nv_bfloat16*)d_in[3];
    prm.v_tree = (const __nv_bfloat16*)d_in[4];
    prm.tree_mask = (const __nv_bfloat16*)d_in[5];
    prm.out = (__nv_bfloat16*)d_out;
    prm.pace = (unsigned int*)pace;
    prm.k_idx = kc < vc ? 0 : 1;
    encode_cache_map(enc, &prm.stage, kc < vc ? kc : vc, kc < vc ? vc : kc, 16);
    tree_attn_kernel<<<kCtas, kThreads, kSmemBytes>>>(prm);
}
```

```cpp
#include <cuda_runtime.h>
#include <cuda_bf16.h>
#include <cuda.h>
#include <stdint.h>

namespace {

constexpr int kB = 8, kHq = 32, kHkv = 8, kC = 8192, kD = 128;
constexpr int kRep = kHq / kHkv;
constexpr int kHeads = kB * kHkv;
constexpr int kCtas = 2 * kHeads;
constexpr int kPieceBytes = 64 * kD * 2;
constexpr int kStageBytes = 2 * kPieceBytes;
constexpr int kStages = 4;
constexpr int kPassStages = 32;
constexpr int kTotal = 2 * kPassStages;
constexpr int kPre = 2;
constexpr int kGroupsPerCta = kC / 2 / 8;
constexpr int kConsumerWarps = 8;
constexpr int kThreads = 32 * (kConsumerWarps + 2);
constexpr int kPitch = kPassStages * 128 * 2 + 16;
constexpr int kPeerPitch = 64 * 2 + 16;
constexpr int kPrefetchBytes = 16384;
constexpr int kPaceTicks = kCtas * 2 * (kTotal - kStages);
constexpr int kPaceLead = (2 * kStages - 1) * kCtas + 232;
constexpr int kPaceStart = 10 * kCtas;
constexpr int kPaceLast = (2 * kTotal - 1) * kCtas;
constexpr int kPacePatience = 400;

constexpr int kOffRing = 0;
constexpr int kOffP = kOffRing + kStages * kStageBytes;
constexpr int kOffPeerP = kOffP + kRep * kPitch;
constexpr int kOffQ = kOffPeerP + kRep * kPeerPitch;
constexpr int kOffX = kOffQ + kRep * kD * 2;
constexpr int kOffWmax = kOffX + 2048;
constexpr int kOffStatL = kOffWmax + 64;
constexpr int kOffStatR = kOffStatL + 64;
constexpr int kOffTree = kOffStatR + 64;
constexpr int kOffKt = kOffTree + 16;
constexpr int kOffVt = kOffKt + kD * 2;
constexpr int kOffMask = kOffVt + kD * 2;
constexpr int kOffPace = kOffMask + 16;
constexpr int kOffBar = kOffPace + 16;
constexpr int kSmemUsed = kOffBar + 8 * (3 * kStages + 2 + kConsumerWarps);
constexpr int kSmemBytes = kSmemUsed + 1024;
static_assert(kSmemBytes <= 232448, "shared memory");

constexpr float kScale = 0.08838834764831845f;
constexpr float kLog2e = 1.4426950408889634f;
constexpr uint32_t kNegInf2 = 0xff80ff80u;
constexpr uint64_t kEvictFirst = 0x12F0000000000000ull;

__device__ unsigned int g_pace[32];

__device__ __forceinline__ uint32_t smem_u32(const void* p) { return (uint32_t)__cvta_generic_to_shared(p); }
__device__ __forceinline__ void mbar_init(uint32_t bar, int cnt) {
    asm volatile("mbarrier.init.shared::cta.b64 [%0], %1;" ::"r"(bar), "r"(cnt) : "memory");
}
__device__ __forceinline__ void mbar_expect_tx(uint32_t bar, uint32_t bytes) {
    asm volatile("mbarrier.arrive.expect_tx.shared::cta.b64 _, [%0], %1;" ::"r"(bar), "r"(bytes) : "memory");
}
__device__ __forceinline__ void mbar_arrive(uint32_t bar) {
    asm volatile("mbarrier.arrive.shared::cta.b64 _, [%0];" ::"r"(bar) : "memory");
}
__device__ __forceinline__ void mbar_wait(uint32_t bar, uint32_t parity) {
    asm volatile(
        "{\n"
        ".reg .pred p;\n"
        ".reg .u32 n;\n"
        "mov.u32 n, 0;\n"
        "WAIT_LOOP:\n"
        "mbarrier.try_wait.parity.shared::cta.b64 p, [%0], %1;\n"
        "@p bra WAIT_DONE;\n"
        "add.u32 n, n, 1;\n"
        "setp.lt.u32 p, n, 0x1000000;\n"
        "@p bra WAIT_LOOP;\n"
        "trap;\n"
        "WAIT_DONE:\n"
        "}\n" ::"r"(bar), "r"(parity) : "memory");
}
__device__ __forceinline__ void mbar_wait_cluster(uint32_t bar, uint32_t parity) {
    asm volatile(
        "{\n"
        ".reg .pred p;\n"
        ".reg .u32 n;\n"
        "mov.u32 n, 0;\n"
        "WAIT_LOOP:\n"
        "mbarrier.try_wait.parity.relaxed.cluster.shared::cta.b64 p, [%0], %1;\n"
        "@p bra WAIT_DONE;\n"
        "add.u32 n, n, 1;\n"
        "setp.lt.u32 p, n, 0x1000000;\n"
        "@p bra WAIT_LOOP;\n"
        "trap;\n"
        "WAIT_DONE:\n"
        "fence.acquire.sync_restrict::shared::cluster.cluster;\n"
        "}\n" ::"r"(bar), "r"(parity) : "memory");
}
__device__ __forceinline__ void tma_box(uint32_t dst, const CUtensorMap* map, int half, int group, uint32_t bar) {
    asm volatile(
        "cp.async.bulk.tensor.4d.shared::cluster.global.mbarrier::complete_tx::bytes.L2::cache_hint [%0], [%1, {%3, %3, %4, %5}], [%2], %6;"
        ::"r"(dst), "l"(map), "r"(bar), "r"(0), "r"(half), "r"(group), "l"(kEvictFirst) : "memory");
}
__device__ __forceinline__ void bulk_copy(uint32_t dst, const void* src, uint32_t bytes, uint32_t bar) {
    asm volatile("cp.async.bulk.shared::cluster.global.mbarrier::complete_tx::bytes [%0], [%1], %2, [%3];"
                 ::"r"(dst), "l"(src), "r"(bytes), "r"(bar) : "memory");
}
__device__ __forceinline__ bool elect_one() {
    uint32_t p;
    asm volatile("{\n.reg .pred p;\nelect.sync _|p, 0xffffffff;\nselp.u32 %0, 1, 0, p;\n}\n" : "=r"(p));
    return p != 0;
}
template <typename T> __device__ __forceinline__ void pin32(T& v) { asm volatile("" : "+r"(v)); }
template <typename T> __device__ __forceinline__ void pin64(T& v) { asm volatile("" : "+l"(v)); }
__device__ __forceinline__ void ldsm_x4(uint32_t addr, uint32_t (&r)[4]) {
    asm volatile("ldmatrix.sync.aligned.m8n8.x4.shared.b16 {%0,%1,%2,%3}, [%4];"
                 : "=r"(r[0]), "=r"(r[1]), "=r"(r[2]), "=r"(r[3]) : "r"(addr) : "memory");
}
__device__ __forceinline__ void ldsm_x4_t(uint32_t addr, uint32_t (&r)[4]) {
    asm volatile("ldmatrix.sync.aligned.m8n8.x4.trans.shared.b16 {%0,%1,%2,%3}, [%4];"
                 : "=r"(r[0]), "=r"(r[1]), "=r"(r[2]), "=r"(r[3]) : "r"(addr) : "memory");
}
__device__ __forceinline__ void stsm_x1_t(uint32_t addr, uint32_t v) {
    asm volatile("stmatrix.sync.aligned.m8n8.x1.trans.shared.b16 [%0], {%1};" ::"r"(addr), "r"(v) : "memory");
}
__device__ __forceinline__ void mma_bf16(float (&c)[4], const uint32_t (&a)[4], uint32_t b0, uint32_t b1) {
    asm volatile("mma.sync.aligned.m16n8k16.row.col.f32.bf16.bf16.f32 {%0,%1,%2,%3}, {%4,%5,%6,%7}, {%8,%9}, {%0,%1,%2,%3};"
                 : "+f"(c[0]), "+f"(c[1]), "+f"(c[2]), "+f"(c[3])
                 : "r"(a[0]), "r"(a[1]), "r"(a[2]), "r"(a[3]), "r"(b0), "r"(b1));
}
__device__ __forceinline__ uint32_t pack_bf16(float lo, float hi) {
    uint32_t r;
    asm("cvt.rn.bf16x2.f32 %0, %1, %2;" : "=r"(r) : "f"(hi), "f"(lo));
    return r;
}
__device__ __forceinline__ float bf_lo(uint32_t v) { return __uint_as_float(v << 16); }
__device__ __forceinline__ float bf_hi(uint32_t v) { return __uint_as_float(v & 0xffff0000u); }
__device__ __forceinline__ uint32_t max_bf16x2(uint32_t a, uint32_t b) {
    uint32_t r;
    asm("max.bf16x2 %0, %1, %2;" : "=r"(r) : "r"(a), "r"(b));
    return r;
}
__device__ __forceinline__ float round_bf16(float x) { return bf_lo(pack_bf16(x, 0.f)); }
__device__ __forceinline__ float exp_diff(float x, float m) {
    float r;
    asm("ex2.approx.ftz.f32 %0, %1;" : "=f"(r) : "f"((x - m) * kLog2e));
    return r;
}
__device__ __forceinline__ uint32_t map_to_cta(uint32_t addr, uint32_t cta) {
    uint32_t r;
    asm("mapa.shared::cluster.u32 %0, %1, %2;" : "=r"(r) : "r"(addr), "r"(cta));
    return r;
}
__device__ __forceinline__ void st_async_u4(uint32_t addr, const uint32_t (&v)[4], uint32_t bar) {
    asm volatile("st.async.weak.shared::cluster.mbarrier::complete_tx::bytes.v4.b32 [%0], {%1, %2, %3, %4}, [%5];"
                 ::"r"(addr), "r"(v[0]), "r"(v[1]), "r"(v[2]), "r"(v[3]), "r"(bar) : "memory");
}
__device__ __forceinline__ void st_async_f2(uint32_t addr, float a, float b, uint32_t bar) {
    asm volatile("st.async.weak.shared::cluster.mbarrier::complete_tx::bytes.v2.f32 [%0], {%1, %2}, [%3];"
                 ::"r"(addr), "f"(a), "f"(b), "r"(bar) : "memory");
}
__device__ __forceinline__ void consumer_sync() { asm volatile("bar.sync 1, 256;" ::: "memory"); }
__device__ __forceinline__ float2 lds_f2(uint32_t addr) {
    float2 v;
    asm volatile("ld.shared.v2.f32 {%0,%1}, [%2];" : "=f"(v.x), "=f"(v.y) : "r"(addr) : "memory");
    return v;
}
__device__ __forceinline__ float4 lds_f4(uint32_t addr) {
    float4 v;
    asm volatile("ld.shared.v4.f32 {%0,%1,%2,%3}, [%4];" : "=f"(v.x), "=f"(v.y), "=f"(v.z), "=f"(v.w) : "r"(addr) : "memory");
    return v;
}
__device__ __forceinline__ void lds_u4(uint32_t addr, uint32_t (&v)[4]) {
    asm volatile("ld.shared.v4.u32 {%0,%1,%2,%3}, [%4];" : "=r"(v[0]), "=r"(v[1]), "=r"(v[2]), "=r"(v[3]) : "r"(addr) : "memory");
}
__device__ __forceinline__ void sts_u4(uint32_t addr, const uint32_t (&v)[4]) {
    asm volatile("st.shared.v4.u32 [%0], {%1,%2,%3,%4};" ::"r"(addr), "r"(v[0]), "r"(v[1]), "r"(v[2]), "r"(v[3]) : "memory");
}
__device__ __forceinline__ void sts_f2(uint32_t addr, float a, float b) {
    asm volatile("st.shared.v2.f32 [%0], {%1,%2};" ::"r"(addr), "f"(a), "f"(b) : "memory");
}
__device__ __forceinline__ int lds_volatile(uint32_t addr) {
    int v;
    asm volatile("ld.volatile.shared.s32 %0, [%1];" : "=r"(v) : "r"(addr) : "memory");
    return v;
}
__device__ __forceinline__ void sts_volatile(uint32_t addr, int v) {
    asm volatile("st.volatile.shared.s32 [%0], %1;" ::"r"(addr), "r"(v) : "memory");
}


struct alignas(64) Params {
    const char* k_raw;
    const __nv_bfloat16 *q, *k_tree, *v_tree, *tree_mask;
    __nv_bfloat16* out;
    unsigned int* pace;
    CUtensorMap piece[2];
    CUtensorMap v_half;
};

__global__ void __cluster_dims__(2, 1, 1) __launch_bounds__(kThreads, 1)
tree_attn_kernel(const __grid_constant__ Params prm) {
    if (threadIdx.x == 0)
        asm volatile("cp.async.bulk.prefetch.L2.global.L2::cache_hint [%0], %1, %2;"
                     ::"l"(prm.k_raw + (size_t)blockIdx.x * (kGroupsPerCta * 2048)), "r"(kPrefetchBytes), "l"(kEvictFirst) : "memory");

    extern __shared__ uint8_t smem_raw[];
    const uint32_t sb = (smem_u32(smem_raw) + 1023u) & ~1023u;
    const uint32_t ring = sb + kOffRing;
    const uint32_t bar_full = sb + kOffBar;
    const uint32_t bar_empty = bar_full + 16 * kStages;
    const uint32_t bar_stat = bar_empty + 8 * kStages;
    const uint32_t bar_q = bar_stat + 8;
    const uint32_t bar_xo = bar_q + 8;
    const int warp = threadIdx.x >> 5, lane = threadIdx.x & 31;
    const int bh = blockIdx.x >> 1;
    const int rank = blockIdx.x & 1;
    const int group0 = blockIdx.x * kGroupsPerCta;

    if (warp == 0) {
        if (elect_one()) {
#pragma unroll
            for (int n = 0; n < 2 * kStages; n++) {
                mbar_init(bar_full + 8 * n, 1);
                mbar_expect_tx(bar_full + 8 * n, kPieceBytes);
                tma_box(ring + n * kPieceBytes, &prm.piece[0], 0, group0 + n * 8, bar_full + 8 * n);
                if (n == 0) {
                    mbar_init(bar_q, 1);
                    mbar_expect_tx(bar_q, kRep * kD * 2 + 2 * kD * 2 + 16);
                    bulk_copy(sb + kOffQ, prm.q + (size_t)bh * kRep * kD, kRep * kD * 2, bar_q);
                }
                if (n == 1) {
                    bulk_copy(sb + kOffKt, prm.k_tree + (size_t)bh * kD, kD * 2, bar_q);
                    bulk_copy(sb + kOffVt, prm.v_tree + (size_t)bh * kD, kD * 2, bar_q);
                    bulk_copy(sb + kOffMask, prm.tree_mask, 16, bar_q);
                }
            }
            asm volatile("prefetch.tensormap [%0];" ::"l"(&prm.piece[1]) : "memory");
            asm volatile("prefetch.tensormap [%0];" ::"l"(&prm.v_half) : "memory");
#pragma unroll
            for (int s = 0; s < kStages; s++) mbar_init(bar_empty + 8 * s, kConsumerWarps);
            mbar_init(bar_stat, 1);
#pragma unroll
            for (int u = 0; u < kConsumerWarps; u++) mbar_init(bar_xo + 8 * u, 1);
            mbar_expect_tx(bar_stat, kConsumerWarps * 8 + kRep * 64 * 2);
#pragma unroll
            for (int u = 0; u < kConsumerWarps; u++) mbar_expect_tx(bar_xo + 8 * u, 32 * 8);
            sts_volatile(sb + kOffPace, kPaceStart);
            sts_volatile(sb + kOffPace + 4, 0);
            asm volatile("fence.mbarrier_init.release.cluster;" ::: "memory");
        }
        __syncwarp();
    }
    __syncthreads();
    asm volatile("barrier.cluster.arrive.relaxed.aligned;" ::: "memory");

    if (warp == 0) {
        if (elect_one()) {
            unsigned int* pace = prm.pace;
            int s = 0, ph = 0, patience = kPacePatience;
#pragma unroll 1
            for (int i = kStages; i < kTotal; i++) {
                mbar_wait(bar_empty + 8 * s, ph);
                const int grp = group0 + (i & (kPassStages - 1)) * 16;
#pragma unroll
                for (int h = 0; h < 2; h++) {
                    while ((2 * i + h) * kCtas > lds_volatile(sb + kOffPace) && patience > 0) { patience--; __nanosleep(20); }
                    if (patience > 0) patience = kPacePatience;
                    const uint32_t dst = ring + s * kStageBytes + h * kPieceBytes, bar = bar_full + 16 * s + 8 * h;
                    mbar_expect_tx(bar, kPieceBytes);
                    if (h == 1 && i == kTotal - 1) {
                        tma_box(dst, &prm.v_half, rank, grp + 8, bar);
                        tma_box(dst + kPieceBytes / 2, &prm.v_half, rank, (grp + 8) ^ kGroupsPerCta, bar);
                    } else {
                        tma_box(dst, &prm.piece[i >> 5], 0, grp + 8 * h, bar);
                    }
                    asm volatile("red.relaxed.gpu.global.inc.u32 [%0], %1;" ::"l"(pace), "r"(kPaceTicks - 1) : "memory");
                }
                if (++s == kStages) { s = 0; ph ^= 1; }
            }
            sts_volatile(sb + kOffPace + 4, 1);
        }
        __syncwarp();
        asm volatile("barrier.cluster.wait.aligned;" ::: "memory");
        return;
    }
    if (warp == 1) {
        asm volatile("barrier.cluster.wait.aligned;" ::: "memory");
        if (elect_one()) {
            const unsigned int* pace = prm.pace;
            int limit = kPaceStart;
#pragma unroll 1
            for (int n = 0; n < (1 << 20) && lds_volatile(sb + kOffPace + 4) == 0; n++) {
                unsigned int ticks;
                asm volatile("ld.relaxed.gpu.global.u32 %0, [%1];" : "=r"(ticks) : "l"(pace) : "memory");
                const int v = kPaceLead + (int)ticks;
                if (v > limit) { limit = v; sts_volatile(sb + kOffPace, v); }
                if (limit >= kPaceLast) break;
                __nanosleep(100);
            }
        }
        return;
    }

    const int w = warp - 2;
    const int g = lane >> 2, t = lane & 3;
    const int mi = lane >> 3, r8 = lane & 7;
    const bool low_half = t < 2;
    const bool keeper = (w >> 2) == rank;
    uint32_t k_off = ring + (2 * w + (mi & 1)) * 2048 + r8 * 128 + (((mi >> 1) ^ r8) << 4);
    const int chunk = 2 * w + (mi & 1);
    uint32_t v_off = ring + (mi >> 1) * 2048 + (chunk >> 3) * 1024 + r8 * 128 + (((chunk & 7) ^ r8) << 4);
    uint32_t s_addr = sb + kOffP + (r8 & 3) * kPitch + (16 * w + 8 * (r8 >> 2)) * 2;
    uint32_t p_addr = sb + kOffP + (r8 & 3) * kPitch + mi * 16;
    pin32(k_off);
    pin32(v_off);
    const int h0 = 2 * (t & 1);
    const int d_own = 16 * w + g + 8 * (t >> 1);
    __nv_bfloat16* outp = prm.out + (size_t)(bh * kRep + h0) * kD + d_own;
    pin64(outp);
    uint32_t x_addr = sb + kOffX + (w * 32 + lane) * 8;
    uint32_t x_bar = bar_xo + 8 * w;
    if (!keeper) { x_addr = map_to_cta(x_addr, rank ^ 1); x_bar = map_to_cta(x_bar, rank ^ 1); }
    pin32(x_addr);
    pin32(x_bar);

    asm volatile("barrier.cluster.wait.aligned;" ::: "memory");
    mbar_wait(bar_q, 0);
    uint32_t qf[4][4];
#pragma unroll
    for (int j = 0; j < 4; j++) ldsm_x4(sb + kOffQ + (r8 & 3) * (kD * 2) + mi * 16 + j * 64, qf[j]);
    if (w < kRep) {
        uint2 qa, ka;
        uint16_t mk16;
        asm volatile("ld.shared.v2.u32 {%0,%1}, [%2];" : "=r"(qa.x), "=r"(qa.y) : "r"(sb + kOffQ + w * (kD * 2) + lane * 8) : "memory");
        asm volatile("ld.shared.v2.u32 {%0,%1}, [%2];" : "=r"(ka.x), "=r"(ka.y) : "r"(sb + kOffKt + lane * 8) : "memory");
        asm volatile("ld.shared.u16 %0, [%1];" : "=h"(mk16) : "r"(sb + kOffMask + (bh / kHkv) * 2) : "memory");
        float sc = bf_lo(qa.x) * bf_lo(ka.x);
        sc = fmaf(bf_hi(qa.x), bf_hi(ka.x), sc);
        sc = fmaf(bf_lo(qa.y), bf_lo(ka.y), sc);
        sc = fmaf(bf_hi(qa.y), bf_hi(ka.y), sc);
#pragma unroll
        for (int o = 16; o > 0; o >>= 1) sc += __shfl_xor_sync(0xffffffffu, sc, o);
        sc = round_bf16(round_bf16(sc) * kScale);
        sc = round_bf16(sc + round_bf16(round_bf16(1.0f - bf_lo(mk16)) * -1000000000.0f));
        if (lane == 0) asm volatile("st.shared.f32 [%0], %1;" ::"r"(sb + kOffTree + 4 * w), "f"(sc) : "memory");
    }

    int s = 0, ph = 0;
    uint32_t mx = kNegInf2;
#pragma unroll 1
    for (int i = 0; i < kPassStages; i++) {
        uint32_t base = k_off + s * kStageBytes;
        pin32(base);
        mbar_wait(bar_full + 16 * s + 8 * (w >> 2), ph);
        float c0[4] = {0.f, 0.f, 0.f, 0.f}, c1[4] = {0.f, 0.f, 0.f, 0.f};
        uint32_t a[8][4];
#pragma unroll
        for (int j = 0; j < 8; j++) ldsm_x4((base ^ ((j & 3) << 5)) + (j >> 2) * 1024, a[j]);
#pragma unroll
        for (int j = 0; j < 8; j += 2) {
            mma_bf16(c0, a[j], qf[j >> 1][0], qf[j >> 1][1]);
            mma_bf16(c1, a[j + 1], qf[j >> 1][2], qf[j >> 1][3]);
        }
        if (lane == 0) mbar_arrive(bar_empty + 8 * s);
        const float x0 = low_half ? c0[0] + c1[0] : c0[2] + c1[2];
        const float x1 = low_half ? c0[1] + c1[1] : c0[3] + c1[3];
        const uint32_t raw = pack_bf16(x0, x1);
        const uint32_t sc = pack_bf16(bf_lo(raw) * kScale, bf_hi(raw) * kScale);
        mx = max_bf16x2(mx, sc);
        stsm_x1_t(s_addr, sc);
        s_addr += 256;
        if (++s == kStages) { s = 0; ph ^= 1; }
    }

    {
#pragma unroll
        for (int o = 2; o < 32; o <<= 1) mx = max_bf16x2(mx, __shfl_xor_sync(0xffffffffu, mx, o));
        if (lane < 2) asm volatile("st.shared.u32 [%0], %1;" ::"r"(sb + kOffWmax + w * 8 + lane * 4), "r"(mx) : "memory");
        consumer_sync();
        const int head = w >> 1;
        uint32_t m2;
        asm volatile("ld.shared.u32 %0, [%1];" : "=r"(m2) : "r"(sb + kOffWmax + r8 * 8 + (head >> 1) * 4) : "memory");
#pragma unroll
        for (int o = 1; o < 8; o <<= 1) m2 = max_bf16x2(m2, __shfl_xor_sync(0xffffffffu, m2, o));
        const float m = (head & 1) ? bf_hi(m2) : bf_lo(m2);
        float sum = 0.f;
        uint32_t addr = sb + kOffP + head * kPitch + (w & 1) * (kPassStages * 128) + lane * 16;
        uint32_t v[4];
#pragma unroll 2
        for (int i = 0; i < kPassStages / 4; i++) {
            lds_u4(addr, v);
#pragma unroll
            for (int j = 0; j < 4; j++) {
                const float e0 = exp_diff(bf_lo(v[j]), m), e1 = exp_diff(bf_hi(v[j]), m);
                sum += e0 + e1;
                v[j] = pack_bf16(e0, e1);
            }
            sts_u4(addr, v);
            addr += 512;
        }
        const uint32_t peer_stat = map_to_cta(bar_stat, rank ^ 1);
        if ((w & 1) && lane >= 24)
            st_async_u4(map_to_cta(sb + kOffPeerP + head * kPeerPitch + (lane - 24) * 16, rank ^ 1), v, peer_stat);
#pragma unroll
        for (int o = 16; o > 0; o >>= 1) sum += __shfl_xor_sync(0xffffffffu, sum, o);
        if (lane == 0) {
            sts_f2(sb + kOffStatL + w * 8, m, sum);
            st_async_f2(map_to_cta(sb + kOffStatR + w * 8, rank ^ 1), m, sum, peer_stat);
        }
        consumer_sync();
    }

    float o0[4] = {0.f, 0.f, 0.f, 0.f}, o1[4] = {0.f, 0.f, 0.f, 0.f};
    float f_loc0 = 0.f, f_loc1 = 0.f, f_rem0 = 0.f, f_rem1 = 0.f, rest0 = 0.f, rest1 = 0.f;
    auto pv_piece = [&](uint32_t base, uint32_t step, const uint32_t (&b0)[4], const uint32_t (&b1)[4],
                        float (&c0)[4], float (&c1)[4]) {
        uint32_t a[4][4];
#pragma unroll
        for (int j = 0; j < 4; j++) ldsm_x4_t(base + j * step, a[j]);
        mma_bf16(c0, a[0], b0[0], b0[1]);
        mma_bf16(c1, a[1], b0[2], b0[3]);
        mma_bf16(c0, a[2], b1[0], b1[1]);
        mma_bf16(c1, a[3], b1[2], b1[3]);
    };
#pragma unroll 1
    for (int i = 0; i < kPassStages - kPre; i++) {
        uint32_t b[4][4];
#pragma unroll
        for (int u = 0; u < 4; u++) ldsm_x4(p_addr + u * 64, b[u]);
        p_addr += 256;
        if (i == 8 && keeper) {
            mbar_wait_cluster(bar_stat, 0);
            const float4 la = lds_f4(sb + kOffStatL + h0 * 16), lb = lds_f4(sb + kOffStatL + h0 * 16 + 16);
            const float4 ra = lds_f4(sb + kOffStatR + h0 * 16), rb = lds_f4(sb + kOffStatR + h0 * 16 + 16);
            const float2 st = lds_f2(sb + kOffTree + h0 * 4);
            uint16_t vt16;
            asm volatile("ld.shared.u16 %0, [%1];" : "=h"(vt16) : "r"(sb + kOffVt + d_own * 2) : "memory");
            const float vt = bf_lo(vt16);
            {
                const float m = fmaxf(fmaxf(la.x, ra.x), st.x);
                const float el = exp_diff(la.x, m), er = exp_diff(ra.x, m), et = exp_diff(st.x, m);
                const float inv = __frcp_rn(el * (la.y + la.w) + er * (ra.y + ra.w) + et);
                f_loc0 = el * inv; f_rem0 = er * inv; rest0 = et * inv * vt;
            }
            {
                const float m = fmaxf(fmaxf(lb.x, rb.x), st.y);
                const float el = exp_diff(lb.x, m), er = exp_diff(rb.x, m), et = exp_diff(st.y, m);
                const float inv = __frcp_rn(el * (lb.y + lb.w) + er * (rb.y + rb.w) + et);
                f_loc1 = el * inv; f_rem1 = er * inv; rest1 = et * inv * vt;
            }
        }
        uint32_t base = v_off + s * kStageBytes;
        pin32(base);
        mbar_wait(bar_full + 16 * s, ph);
        pv_piece(base, 4096, b[0], b[1], o0, o1);
        mbar_wait(bar_full + 16 * s + 8, ph);
        pv_piece(base + kPieceBytes, 4096, b[2], b[3], o0, o1);
        if (lane == 0) mbar_arrive(bar_empty + 8 * s);
        if (++s == kStages) { s = 0; ph ^= 1; }
    }
    uint32_t b[4 * kPre][4];
#pragma unroll
    for (int u = 0; u < 4 * kPre; u++) ldsm_x4(p_addr + u * 64, b[u]);
#pragma unroll
    for (int n = 0; n < 2 * kPre - 1; n++) {
        const int i = kTotal - kPre + (n >> 1);
        mbar_wait(bar_full + 16 * (i % kStages) + 8 * (n & 1), (i / kStages) & 1);
        pv_piece(v_off + (i % kStages) * kStageBytes + (n & 1) * kPieceBytes, 4096, b[2 * n], b[2 * n + 1], o0, o1);
        if ((n & 1) && i + kStages < kTotal && lane == 0) mbar_arrive(bar_empty + 8 * (i % kStages));
    }
    if (!keeper) {
        st_async_f2(x_addr, low_half ? o0[0] + o1[0] : o0[2] + o1[2], low_half ? o0[1] + o1[1] : o0[3] + o1[3], x_bar);
        return;
    }
    constexpr int kLast = kTotal - 1;
    uint32_t pb[2][4];
#pragma unroll
    for (int u = 0; u < 2; u++) ldsm_x4(sb + kOffPeerP + (r8 & 3) * kPeerPitch + mi * 16 + u * 64, pb[u]);
    uint32_t base = ring + (kLast % kStages) * kStageBytes + kPieceBytes + (mi >> 1) * 1024 + r8 * 128 + (((chunk & 7) ^ r8) << 4);
    pin32(base);
    mbar_wait_cluster(x_bar, 0);
    const float2 rem = lds_f2(x_addr);
    float q0[4] = {0.f, 0.f, 0.f, 0.f}, q1[4] = {0.f, 0.f, 0.f, 0.f};
    rest0 = fmaf(rem.x, f_rem0, rest0);
    rest1 = fmaf(rem.y, f_rem1, rest1);
    mbar_wait(bar_full + 16 * (kLast % kStages) + 8, (kLast / kStages) & 1);
    pv_piece(base, 2048, b[4 * kPre - 2], b[4 * kPre - 1], o0, o1);
    pv_piece(base + kPieceBytes / 2, 2048, pb[0], pb[1], q0, q1);
    const float y0 = fmaf(low_half ? q0[0] + q1[0] : q0[2] + q1[2], f_rem0,
                          fmaf(low_half ? o0[0] + o1[0] : o0[2] + o1[2], f_loc0, rest0));
    const float y1 = fmaf(low_half ? q0[1] + q1[1] : q0[3] + q1[3], f_rem1,
                          fmaf(low_half ? o0[1] + o1[1] : o0[3] + o1[3], f_loc1, rest1));
    const uint32_t pk = pack_bf16(y0, y1);
    asm volatile("st.global.u16 [%0], %1;" ::"l"(outp), "h"((uint16_t)pk) : "memory");
    asm volatile("st.global.u16 [%0 + 256], %1;" ::"l"(outp), "h"((uint16_t)(pk >> 16)) : "memory");
}

typedef CUresult (*EncodeTiledFn)(CUtensorMap*, CUtensorMapDataType, cuuint32_t, void*, const cuuint64_t*,
                                  const cuuint64_t*, const cuuint32_t*, const cuuint32_t*, CUtensorMapInterleave,
                                  CUtensorMapSwizzle, CUtensorMapL2promotion, CUtensorMapFloatOOBfill);

void encode_cache_map(EncodeTiledFn enc, CUtensorMap* map, const void* base, int halves) {
    const cuuint64_t dims[4] = {64, 8, 2, (cuuint64_t)kHeads * kC / 8};
    const cuuint64_t strides[3] = {256, 128, 2048};
    const cuuint32_t box[4] = {64, 8, (cuuint32_t)halves, 8};
    const cuuint32_t estr[4] = {1, 1, 1, 1};
    enc(map, CU_TENSOR_MAP_DATA_TYPE_BFLOAT16, 4, const_cast<void*>(base), dims, strides, box, estr,
        CU_TENSOR_MAP_INTERLEAVE_NONE, CU_TENSOR_MAP_SWIZZLE_128B, CU_TENSOR_MAP_L2_PROMOTION_NONE,
        CU_TENSOR_MAP_FLOAT_OOB_FILL_NONE);
}

}

extern "C" void kernel_launch(void* const* d_in, const int* in_sizes, int n_in, void* d_out, int out_size) {
    (void)in_sizes; (void)n_in; (void)out_size;
    static EncodeTiledFn enc = nullptr;
    static void* pace = nullptr;
    if (!enc) {
        void* fn = nullptr;
        cudaDriverEntryPointQueryResult qr;
        cudaGetDriverEntryPoint("cuTensorMapEncodeTiled", &fn, cudaEnableDefault, &qr);
        enc = (EncodeTiledFn)fn;
        cudaGetSymbolAddress(&pace, g_pace);
        cudaFuncSetAttribute(tree_attn_kernel, cudaFuncAttributeMaxDynamicSharedMemorySize, kSmemBytes);
    }
    Params prm;
    prm.k_raw = (const char*)d_in[1];
    prm.q = (const __nv_bfloat16*)d_in[0];
    prm.k_tree = (const __nv_bfloat16*)d_in[3];
    prm.v_tree = (const __nv_bfloat16*)d_in[4];
    prm.tree_mask = (const __nv_bfloat16*)d_in[5];
    prm.out = (__nv_bfloat16*)d_out;
    prm.pace = (unsigned int*)pace;
    encode_cache_map(enc, &prm.piece[0], d_in[1], 2);
    encode_cache_map(enc, &prm.piece[1], d_in[2], 2);
    encode_cache_map(enc, &prm.v_half, d_in[2], 1);
    tree_attn_kernel<<<kCtas, kThreads, kSmemBytes>>>(prm);
}
```

```cpp
#include <cuda_runtime.h>
#include <cuda_bf16.h>
#include <cuda.h>
#include <stdint.h>

namespace {

constexpr int kB = 8, kHq = 32, kHkv = 8, kC = 8192, kD = 128;
constexpr int kRep = kHq / kHkv;
constexpr int kHeads = kB * kHkv;
constexpr int kCtas = 2 * kHeads;
constexpr int kPieceBytes = 64 * kD * 2;
constexpr int kStageBytes = 2 * kPieceBytes;
constexpr int kStages = 4;
constexpr int kPassStages = 32;
constexpr int kTotal = 2 * kPassStages;
constexpr int kPre = 2;
constexpr int kGroupsPerCta = kC / 2 / 8;
constexpr int kConsumerWarps = 8;
constexpr int kThreads = 32 * (kConsumerWarps + 2);
constexpr int kPitch = kPassStages * 128 * 2 + 16;
constexpr int kPeerPitch = 64 * 2 + 16;
constexpr int kPrefetchBytes = 16384;
constexpr int kPaceTicks = kCtas * 2 * (kTotal - kStages);
constexpr int kPaceLead = (2 * kStages - 1) * kCtas + 232;
constexpr int kPaceStart = 10 * kCtas;
constexpr int kPaceLast = (2 * kTotal - 1) * kCtas + 48;
constexpr int kPacePatience = 400;

constexpr int kOffRing = 0;
constexpr int kOffP = kOffRing + kStages * kStageBytes;
constexpr int kOffPeerP = kOffP + kRep * kPitch;
constexpr int kOffQ = kOffPeerP + kRep * kPeerPitch;
constexpr int kOffX = kOffQ + kRep * kD * 2;
constexpr int kOffWmax = kOffX + 2048;
constexpr int kOffStatL = kOffWmax + 64;
constexpr int kOffStatR = kOffStatL + 64;
constexpr int kOffTree = kOffStatR + 64;
constexpr int kOffKt = kOffTree + 16;
constexpr int kOffVt = kOffKt + kD * 2;
constexpr int kOffMask = kOffVt + kD * 2;
constexpr int kOffPace = kOffMask + 16;
constexpr int kOffBar = kOffPace + 16;
constexpr int kSmemUsed = kOffBar + 8 * (3 * kStages + 2 + kConsumerWarps);
constexpr int kSmemBytes = kSmemUsed + 1024;
static_assert(kSmemBytes <= 232448, "shared memory");

constexpr float kScale = 0.08838834764831845f;
constexpr float kLog2e = 1.4426950408889634f;
constexpr uint32_t kNegInf2 = 0xff80ff80u;

__device__ unsigned int g_pace[32];

__device__ __forceinline__ uint32_t smem_u32(const void* p) { return (uint32_t)__cvta_generic_to_shared(p); }
__device__ __forceinline__ void mbar_init(uint32_t bar, int cnt) {
    asm volatile("mbarrier.init.shared::cta.b64 [%0], %1;" ::"r"(bar), "r"(cnt) : "memory");
}
__device__ __forceinline__ void mbar_expect_tx(uint32_t bar, uint32_t bytes) {
    asm volatile("mbarrier.arrive.expect_tx.shared::cta.b64 _, [%0], %1;" ::"r"(bar), "r"(bytes) : "memory");
}
__device__ __forceinline__ void mbar_arrive(uint32_t bar) {
    asm volatile("mbarrier.arrive.shared::cta.b64 _, [%0];" ::"r"(bar) : "memory");
}
__device__ __forceinline__ void mbar_wait(uint32_t bar, uint32_t parity) {
    asm volatile(
        "{\n"
        ".reg .pred p;\n"
        ".reg .u32 n;\n"
        "mov.u32 n, 0;\n"
        "WAIT_LOOP:\n"
        "mbarrier.try_wait.parity.shared::cta.b64 p, [%0], %1;\n"
        "@p bra WAIT_DONE;\n"
        "add.u32 n, n, 1;\n"
        "setp.lt.u32 p, n, 0x1000000;\n"
        "@p bra WAIT_LOOP;\n"
        "trap;\n"
        "WAIT_DONE:\n"
        "}\n" ::"r"(bar), "r"(parity) : "memory");
}
__device__ __forceinline__ void mbar_wait_cluster(uint32_t bar, uint32_t parity) {
    asm volatile(
        "{\n"
        ".reg .pred p;\n"
        ".reg .u32 n;\n"
        "mov.u32 n, 0;\n"
        "WAIT_LOOP:\n"
        "mbarrier.try_wait.parity.relaxed.cluster.shared::cta.b64 p, [%0], %1;\n"
        "@p bra WAIT_DONE;\n"
        "add.u32 n, n, 1;\n"
        "setp.lt.u32 p, n, 0x1000000;\n"
        "@p bra WAIT_LOOP;\n"
        "trap;\n"
        "WAIT_DONE:\n"
        "fence.acquire.sync_restrict::shared::cluster.cluster;\n"
        "}\n" ::"r"(bar), "r"(parity) : "memory");
}
__device__ __forceinline__ uint64_t evict_first_policy() {
    uint64_t p;
    asm("createpolicy.fractional.L2::evict_first.b64 %0, 1.0;" : "=l"(p));
    return p;
}
__device__ __forceinline__ void tma_box(uint32_t dst, const CUtensorMap* map, int half, int group, uint32_t bar) {
    asm volatile(
        "cp.async.bulk.tensor.4d.shared::cluster.global.mbarrier::complete_tx::bytes.L2::cache_hint [%0], [%1, {%3, %3, %4, %5}], [%2], %6;"
        ::"r"(dst), "l"(map), "r"(bar), "r"(0), "r"(half), "r"(group), "l"(evict_first_policy()) : "memory");
}
__device__ __forceinline__ void bulk_copy(uint32_t dst, const void* src, uint32_t bytes, uint32_t bar) {
    asm volatile("cp.async.bulk.shared::cluster.global.mbarrier::complete_tx::bytes [%0], [%1], %2, [%3];"
                 ::"r"(dst), "l"(src), "r"(bytes), "r"(bar) : "memory");
}
__device__ __forceinline__ bool elect_one() {
    uint32_t p;
    asm volatile("{\n.reg .pred p;\nelect.sync _|p, 0xffffffff;\nselp.u32 %0, 1, 0, p;\n}\n" : "=r"(p));
    return p != 0;
}
template <typename T> __device__ __forceinline__ void pin32(T& v) { asm volatile("" : "+r"(v)); }
template <typename T> __device__ __forceinline__ void pin64(T& v) { asm volatile("" : "+l"(v)); }
__device__ __forceinline__ void ldsm_x4(uint32_t addr, uint32_t (&r)[4]) {
    asm volatile("ldmatrix.sync.aligned.m8n8.x4.shared.b16 {%0,%1,%2,%3}, [%4];"
                 : "=r"(r[0]), "=r"(r[1]), "=r"(r[2]), "=r"(r[3]) : "r"(addr) : "memory");
}
__device__ __forceinline__ void ldsm_x4_t(uint32_t addr, uint32_t (&r)[4]) {
    asm volatile("ldmatrix.sync.aligned.m8n8.x4.trans.shared.b16 {%0,%1,%2,%3}, [%4];"
                 : "=r"(r[0]), "=r"(r[1]), "=r"(r[2]), "=r"(r[3]) : "r"(addr) : "memory");
}
__device__ __forceinline__ void stsm_x1_t(uint32_t addr, uint32_t v) {
    asm volatile("stmatrix.sync.aligned.m8n8.x1.trans.shared.b16 [%0], {%1};" ::"r"(addr), "r"(v) : "memory");
}
__device__ __forceinline__ void mma_bf16(float (&c)[4], const uint32_t (&a)[4], uint32_t b0, uint32_t b1) {
    asm volatile("mma.sync.aligned.m16n8k16.row.col.f32.bf16.bf16.f32 {%0,%1,%2,%3}, {%4,%5,%6,%7}, {%8,%9}, {%0,%1,%2,%3};"
                 : "+f"(c[0]), "+f"(c[1]), "+f"(c[2]), "+f"(c[3])
                 : "r"(a[0]), "r"(a[1]), "r"(a[2]), "r"(a[3]), "r"(b0), "r"(b1));
}
__device__ __forceinline__ uint32_t pack_bf16(float lo, float hi) {
    uint32_t r;
    asm("cvt.rn.bf16x2.f32 %0, %1, %2;" : "=r"(r) : "f"(hi), "f"(lo));
    return r;
}
__device__ __forceinline__ float bf_lo(uint32_t v) { return __uint_as_float(v << 16); }
__device__ __forceinline__ float bf_hi(uint32_t v) { return __uint_as_float(v & 0xffff0000u); }
__device__ __forceinline__ uint32_t max_bf16x2(uint32_t a, uint32_t b) {
    uint32_t r;
    asm("max.bf16x2 %0, %1, %2;" : "=r"(r) : "r"(a), "r"(b));
    return r;
}
__device__ __forceinline__ float round_bf16(float x) { return bf_lo(pack_bf16(x, 0.f)); }
__device__ __forceinline__ float exp_diff(float x, float m) {
    float r;
    asm("ex2.approx.ftz.f32 %0, %1;" : "=f"(r) : "f"((x - m) * kLog2e));
    return r;
}
__device__ __forceinline__ uint32_t map_to_cta(uint32_t addr, uint32_t cta) {
    uint32_t r;
    asm("mapa.shared::cluster.u32 %0, %1, %2;" : "=r"(r) : "r"(addr), "r"(cta));
    return r;
}
__device__ __forceinline__ void st_async_u4(uint32_t addr, const uint32_t (&v)[4], uint32_t bar) {
    asm volatile("st.async.weak.shared::cluster.mbarrier::complete_tx::bytes.v4.b32 [%0], {%1, %2, %3, %4}, [%5];"
                 ::"r"(addr), "r"(v[0]), "r"(v[1]), "r"(v[2]), "r"(v[3]), "r"(bar) : "memory");
}
__device__ __forceinline__ void st_async_f2(uint32_t addr, float a, float b, uint32_t bar) {
    asm volatile("st.async.weak.shared::cluster.mbarrier::complete_tx::bytes.v2.f32 [%0], {%1, %2}, [%3];"
                 ::"r"(addr), "f"(a), "f"(b), "r"(bar) : "memory");
}
__device__ __forceinline__ void consumer_sync() { asm volatile("bar.sync 1, 256;" ::: "memory"); }
__device__ __forceinline__ float2 lds_f2(uint32_t addr) {
    float2 v;
    asm volatile("ld.shared.v2.f32 {%0,%1}, [%2];" : "=f"(v.x), "=f"(v.y) : "r"(addr) : "memory");
    return v;
}
__device__ __forceinline__ float4 lds_f4(uint32_t addr) {
    float4 v;
    asm volatile("ld.shared.v4.f32 {%0,%1,%2,%3}, [%4];" : "=f"(v.x), "=f"(v.y), "=f"(v.z), "=f"(v.w) : "r"(addr) : "memory");
    return v;
}
__device__ __forceinline__ void lds_u4(uint32_t addr, uint32_t (&v)[4]) {
    asm volatile("ld.shared.v4.u32 {%0,%1,%2,%3}, [%4];" : "=r"(v[0]), "=r"(v[1]), "=r"(v[2]), "=r"(v[3]) : "r"(addr) : "memory");
}
__device__ __forceinline__ void sts_u4(uint32_t addr, const uint32_t (&v)[4]) {
    asm volatile("st.shared.v4.u32 [%0], {%1,%2,%3,%4};" ::"r"(addr), "r"(v[0]), "r"(v[1]), "r"(v[2]), "r"(v[3]) : "memory");
}
__device__ __forceinline__ void sts_f2(uint32_t addr, float a, float b) {
    asm volatile("st.shared.v2.f32 [%0], {%1,%2};" ::"r"(addr), "f"(a), "f"(b) : "memory");
}
__device__ __forceinline__ int lds_volatile(uint32_t addr) {
    int v;
    asm volatile("ld.volatile.shared.s32 %0, [%1];" : "=r"(v) : "r"(addr) : "memory");
    return v;
}
__device__ __forceinline__ void sts_volatile(uint32_t addr, int v) {
    asm volatile("st.volatile.shared.s32 [%0], %1;" ::"r"(addr), "r"(v) : "memory");
}


struct alignas(64) Params {
    const char* k_raw;
    const __nv_bfloat16 *q, *k_tree, *v_tree, *tree_mask;
    __nv_bfloat16* out;
    unsigned int* pace;
    CUtensorMap piece[2];
    CUtensorMap v_half;
};

__global__ void __cluster_dims__(2, 1, 1) __launch_bounds__(kThreads, 1)
tree_attn_kernel(const __grid_constant__ Params prm) {
    if (threadIdx.x == 0)
        asm volatile("cp.async.bulk.prefetch.L2.global [%0], %1;"
                     ::"l"(prm.k_raw + (size_t)blockIdx.x * (kGroupsPerCta * 2048)), "r"(kPrefetchBytes) : "memory");

    extern __shared__ uint8_t smem_raw[];
    const uint32_t sb = (smem_u32(smem_raw) + 1023u) & ~1023u;
    const uint32_t ring = sb + kOffRing;
    const uint32_t bar_full = sb + kOffBar;
    const uint32_t bar_empty = bar_full + 16 * kStages;
    const uint32_t bar_stat = bar_empty + 8 * kStages;
    const uint32_t bar_q = bar_stat + 8;
    const uint32_t bar_xo = bar_q + 8;
    const int warp = threadIdx.x >> 5, lane = threadIdx.x & 31;
    const int bh = blockIdx.x >> 1;
    const int rank = blockIdx.x & 1;
    const int group0 = blockIdx.x * kGroupsPerCta;

    if (warp == 0) {
        if (elect_one()) {
#pragma unroll
            for (int n = 0; n < 2 * kStages; n++) {
                mbar_init(bar_full + 8 * n, 1);
                mbar_expect_tx(bar_full + 8 * n, kPieceBytes);
                tma_box(ring + n * kPieceBytes, &prm.piece[0], 0, group0 + n * 8, bar_full + 8 * n);
                if (n == 0) {
                    mbar_init(bar_q, 1);
                    mbar_expect_tx(bar_q, kRep * kD * 2 + 2 * kD * 2 + 16);
                    bulk_copy(sb + kOffQ, prm.q + (size_t)bh * kRep * kD, kRep * kD * 2, bar_q);
                }
                if (n == 1) {
                    bulk_copy(sb + kOffKt, prm.k_tree + (size_t)bh * kD, kD * 2, bar_q);
                    bulk_copy(sb + kOffVt, prm.v_tree + (size_t)bh * kD, kD * 2, bar_q);
                    bulk_copy(sb + kOffMask, prm.tree_mask, 16, bar_q);
                }
            }
            asm volatile("prefetch.tensormap [%0];" ::"l"(&prm.piece[1]) : "memory");
            asm volatile("prefetch.tensormap [%0];" ::"l"(&prm.v_half) : "memory");
#pragma unroll
            for (int s = 0; s < kStages; s++) mbar_init(bar_empty + 8 * s, kConsumerWarps);
            mbar_init(bar_stat, 1);
#pragma unroll
            for (int u = 0; u < kConsumerWarps; u++) mbar_init(bar_xo + 8 * u, 1);
            mbar_expect_tx(bar_stat, kConsumerWarps * 8 + kRep * 64 * 2);
#pragma unroll
            for (int u = 0; u < kConsumerWarps; u++) mbar_expect_tx(bar_xo + 8 * u, 32 * 8);
            sts_volatile(sb + kOffPace, kPaceStart);
            sts_volatile(sb + kOffPace + 4, 0);
            asm volatile("fence.mbarrier_init.release.cluster;" ::: "memory");
        }
        __syncwarp();
    }
    __syncthreads();
    asm volatile("barrier.cluster.arrive.relaxed.aligned;" ::: "memory");

    if (warp == 0) {
        if (elect_one()) {
            unsigned int* pace = prm.pace;
            int s = 0, ph = 0, patience = kPacePatience;
#pragma unroll 1
            for (int i = kStages; i < kTotal; i++) {
                mbar_wait(bar_empty + 8 * s, ph);
                const int grp = group0 + (i & (kPassStages - 1)) * 16;
#pragma unroll
                for (int h = 0; h < 2; h++) {
                    const bool last = h == 1 && i == kTotal - 1;
                    const int need = last ? kPaceLast : (2 * i + h) * kCtas;
                    while (need > lds_volatile(sb + kOffPace) && patience > 0) { patience--; __nanosleep(20); }
                    if (patience > 0) patience = kPacePatience;
                    const uint32_t dst = ring + s * kStageBytes + h * kPieceBytes, bar = bar_full + 16 * s + 8 * h;
                    mbar_expect_tx(bar, kPieceBytes);
                    if (last) {
                        tma_box(dst, &prm.v_half, rank, grp + 8, bar);
                        tma_box(dst + kPieceBytes / 2, &prm.v_half, rank, (grp + 8) ^ kGroupsPerCta, bar);
                    } else {
                        tma_box(dst, &prm.piece[i >> 5], 0, grp + 8 * h, bar);
                    }
                    asm volatile("red.relaxed.gpu.global.inc.u32 [%0], %1;" ::"l"(pace), "r"(kPaceTicks - 1) : "memory");
                }
                if (++s == kStages) { s = 0; ph ^= 1; }
            }
            sts_volatile(sb + kOffPace + 4, 1);
        }
        __syncwarp();
        asm volatile("barrier.cluster.wait.aligned;" ::: "memory");
        return;
    }
    if (warp == 1) {
        asm volatile("barrier.cluster.wait.aligned;" ::: "memory");
        if (elect_one()) {
            const unsigned int* pace = prm.pace;
            int limit = kPaceStart;
#pragma unroll 1
            for (int n = 0; n < (1 << 20) && lds_volatile(sb + kOffPace + 4) == 0; n++) {
                unsigned int ticks;
                asm volatile("ld.relaxed.gpu.global.u32 %0, [%1];" : "=r"(ticks) : "l"(pace) : "memory");
                const int v = kPaceLead + (int)ticks;
                if (v > limit) { limit = v; sts_volatile(sb + kOffPace, v); }
                if (limit >= kPaceLast) break;
                __nanosleep(100);
            }
        }
        return;
    }

    const int w = warp - 2;
    const int g = lane >> 2, t = lane & 3;
    const int mi = lane >> 3, r8 = lane & 7;
    const bool low_half = t < 2;
    const bool keeper = (w >> 2) == rank;
    uint32_t k_off = ring + (2 * w + (mi & 1)) * 2048 + r8 * 128 + (((mi >> 1) ^ r8) << 4);
    const int chunk = 2 * w + (mi & 1);
    uint32_t v_off = ring + (mi >> 1) * 2048 + (chunk >> 3) * 1024 + r8 * 128 + (((chunk & 7) ^ r8) << 4);
    uint32_t s_addr = sb + kOffP + (r8 & 3) * kPitch + (16 * w + 8 * (r8 >> 2)) * 2;
    uint32_t p_addr = sb + kOffP + (r8 & 3) * kPitch + mi * 16;
    pin32(k_off);
    pin32(v_off);
    const int h0 = 2 * (t & 1);
    const int d_own = 16 * w + g + 8 * (t >> 1);
    __nv_bfloat16* outp = prm.out + (size_t)(bh * kRep + h0) * kD + d_own;
    pin64(outp);
    uint32_t x_addr = sb + kOffX + (w * 32 + lane) * 8;
    uint32_t x_bar = bar_xo + 8 * w;
    if (!keeper) { x_addr = map_to_cta(x_addr, rank ^ 1); x_bar = map_to_cta(x_bar, rank ^ 1); }
    pin32(x_addr);
    pin32(x_bar);

    asm volatile("barrier.cluster.wait.aligned;" ::: "memory");
    mbar_wait(bar_q, 0);
    uint32_t qf[4][4];
#pragma unroll
    for (int j = 0; j < 4; j++) ldsm_x4(sb + kOffQ + (r8 & 3) * (kD * 2) + mi * 16 + j * 64, qf[j]);
    if (w < kRep) {
        uint2 qa, ka;
        uint16_t mk16;
        asm volatile("ld.shared.v2.u32 {%0,%1}, [%2];" : "=r"(qa.x), "=r"(qa.y) : "r"(sb + kOffQ + w * (kD * 2) + lane * 8) : "memory");
        asm volatile("ld.shared.v2.u32 {%0,%1}, [%2];" : "=r"(ka.x), "=r"(ka.y) : "r"(sb + kOffKt + lane * 8) : "memory");
        asm volatile("ld.shared.u16 %0, [%1];" : "=h"(mk16) : "r"(sb + kOffMask + (bh / kHkv) * 2) : "memory");
        float sc = bf_lo(qa.x) * bf_lo(ka.x);
        sc = fmaf(bf_hi(qa.x), bf_hi(ka.x), sc);
        sc = fmaf(bf_lo(qa.y), bf_lo(ka.y), sc);
        sc = fmaf(bf_hi(qa.y), bf_hi(ka.y), sc);
#pragma unroll
        for (int o = 16; o > 0; o >>= 1) sc += __shfl_xor_sync(0xffffffffu, sc, o);
        sc = round_bf16(round_bf16(sc) * kScale);
        sc = round_bf16(sc + round_bf16(round_bf16(1.0f - bf_lo(mk16)) * -1000000000.0f));
        if (lane == 0) asm volatile("st.shared.f32 [%0], %1;" ::"r"(sb + kOffTree + 4 * w), "f"(sc) : "memory");
    }

    int s = 0, ph = 0;
    uint32_t mx = kNegInf2;
#pragma unroll 1
    for (int i = 0; i < kPassStages; i++) {
        uint32_t base = k_off + s * kStageBytes;
        pin32(base);
        mbar_wait(bar_full + 16 * s + 8 * (w >> 2), ph);
        float c0[4] = {0.f, 0.f, 0.f, 0.f}, c1[4] = {0.f, 0.f, 0.f, 0.f};
        uint32_t a[8][4];
#pragma unroll
        for (int j = 0; j < 8; j++) ldsm_x4((base ^ ((j & 3) << 5)) + (j >> 2) * 1024, a[j]);
#pragma unroll
        for (int j = 0; j < 8; j += 2) {
            mma_bf16(c0, a[j], qf[j >> 1][0], qf[j >> 1][1]);
            mma_bf16(c1, a[j + 1], qf[j >> 1][2], qf[j >> 1][3]);
        }
        if (lane == 0) mbar_arrive(bar_empty + 8 * s);
        const float x0 = low_half ? c0[0] + c1[0] : c0[2] + c1[2];
        const float x1 = low_half ? c0[1] + c1[1] : c0[3] + c1[3];
        const uint32_t raw = pack_bf16(x0, x1);
        const uint32_t sc = pack_bf16(bf_lo(raw) * kScale, bf_hi(raw) * kScale);
        mx = max_bf16x2(mx, sc);
        stsm_x1_t(s_addr, sc);
        s_addr += 256;
        if (++s == kStages) { s = 0; ph ^= 1; }
    }

    {
#pragma unroll
        for (int o = 2; o < 32; o <<= 1) mx = max_bf16x2(mx, __shfl_xor_sync(0xffffffffu, mx, o));
        if (lane < 2) asm volatile("st.shared.u32 [%0], %1;" ::"r"(sb + kOffWmax + w * 8 + lane * 4), "r"(mx) : "memory");
        consumer_sync();
        const int head = w >> 1;
        uint32_t m2;
        asm volatile("ld.shared.u32 %0, [%1];" : "=r"(m2) : "r"(sb + kOffWmax + r8 * 8 + (head >> 1) * 4) : "memory");
#pragma unroll
        for (int o = 1; o < 8; o <<= 1) m2 = max_bf16x2(m2, __shfl_xor_sync(0xffffffffu, m2, o));
        const float m = (head & 1) ? bf_hi(m2) : bf_lo(m2);
        float sum = 0.f;
        uint32_t addr = sb + kOffP + head * kPitch + (w & 1) * (kPassStages * 128) + lane * 16;
        uint32_t v[4];
#pragma unroll 2
        for (int i = 0; i < kPassStages / 4; i++) {
            lds_u4(addr, v);
#pragma unroll
            for (int j = 0; j < 4; j++) {
                const float e0 = exp_diff(bf_lo(v[j]), m), e1 = exp_diff(bf_hi(v[j]), m);
                sum += e0 + e1;
                v[j] = pack_bf16(e0, e1);
            }
            sts_u4(addr, v);
            addr += 512;
        }
        const uint32_t peer_stat = map_to_cta(bar_stat, rank ^ 1);
        if ((w & 1) && lane >= 24)
            st_async_u4(map_to_cta(sb + kOffPeerP + head * kPeerPitch + (lane - 24) * 16, rank ^ 1), v, peer_stat);
#pragma unroll
        for (int o = 16; o > 0; o >>= 1) sum += __shfl_xor_sync(0xffffffffu, sum, o);
        if (lane == 0) {
            sts_f2(sb + kOffStatL + w * 8, m, sum);
            st_async_f2(map_to_cta(sb + kOffStatR + w * 8, rank ^ 1), m, sum, peer_stat);
        }
        consumer_sync();
    }

    float o0[4] = {0.f, 0.f, 0.f, 0.f}, o1[4] = {0.f, 0.f, 0.f, 0.f};
    float f_loc0 = 0.f, f_loc1 = 0.f, f_rem0 = 0.f, f_rem1 = 0.f, rest0 = 0.f, rest1 = 0.f;
    auto pv_piece = [&](uint32_t base, uint32_t step, const uint32_t (&b0)[4], const uint32_t (&b1)[4],
                        float (&c0)[4], float (&c1)[4]) {
        uint32_t a[4][4];
#pragma unroll
        for (int j = 0; j < 4; j++) ldsm_x4_t(base + j * step, a[j]);
        mma_bf16(c0, a[0], b0[0], b0[1]);
        mma_bf16(c1, a[1], b0[2], b0[3]);
        mma_bf16(c0, a[2], b1[0], b1[1]);
        mma_bf16(c1, a[3], b1[2], b1[3]);
    };
#pragma unroll 1
    for (int i = 0; i < kPassStages - kPre; i++) {
        uint32_t b[4][4];
#pragma unroll
        for (int u = 0; u < 4; u++) ldsm_x4(p_addr + u * 64, b[u]);
        p_addr += 256;
        if (i == 8 && keeper) {
            mbar_wait_cluster(bar_stat, 0);
            const float4 la = lds_f4(sb + kOffStatL + h0 * 16), lb = lds_f4(sb + kOffStatL + h0 * 16 + 16);
            const float4 ra = lds_f4(sb + kOffStatR + h0 * 16), rb = lds_f4(sb + kOffStatR + h0 * 16 + 16);
            const float2 st = lds_f2(sb + kOffTree + h0 * 4);
            uint16_t vt16;
            asm volatile("ld.shared.u16 %0, [%1];" : "=h"(vt16) : "r"(sb + kOffVt + d_own * 2) : "memory");
            const float vt = bf_lo(vt16);
            {
                const float m = fmaxf(fmaxf(la.x, ra.x), st.x);
                const float el = exp_diff(la.x, m), er = exp_diff(ra.x, m), et = exp_diff(st.x, m);
                const float inv = __frcp_rn(el * (la.y + la.w) + er * (ra.y + ra.w) + et);
                f_loc0 = el * inv; f_rem0 = er * inv; rest0 = et * inv * vt;
            }
            {
                const float m = fmaxf(fmaxf(lb.x, rb.x), st.y);
                const float el = exp_diff(lb.x, m), er = exp_diff(rb.x, m), et = exp_diff(st.y, m);
                const float inv = __frcp_rn(el * (lb.y + lb.w) + er * (rb.y + rb.w) + et);
                f_loc1 = el * inv; f_rem1 = er * inv; rest1 = et * inv * vt;
            }
        }
        uint32_t base = v_off + s * kStageBytes;
        pin32(base);
        mbar_wait(bar_full + 16 * s, ph);
        pv_piece(base, 4096, b[0], b[1], o0, o1);
        mbar_wait(bar_full + 16 * s + 8, ph);
        pv_piece(base + kPieceBytes, 4096, b[2], b[3], o0, o1);
        if (lane == 0) mbar_arrive(bar_empty + 8 * s);
        if (++s == kStages) { s = 0; ph ^= 1; }
    }
    uint32_t b[4 * kPre][4];
#pragma unroll
    for (int u = 0; u < 4 * kPre; u++) ldsm_x4(p_addr + u * 64, b[u]);
#pragma unroll
    for (int n = 0; n < 2 * kPre - 1; n++) {
        const int i = kTotal - kPre + (n >> 1);
        mbar_wait(bar_full + 16 * (i % kStages) + 8 * (n & 1), (i / kStages) & 1);
        pv_piece(v_off + (i % kStages) * kStageBytes + (n & 1) * kPieceBytes, 4096, b[2 * n], b[2 * n + 1], o0, o1);
        if ((n & 1) && i + kStages < kTotal && lane == 0) mbar_arrive(bar_empty + 8 * (i % kStages));
    }
    if (!keeper) {
        st_async_f2(x_addr, low_half ? o0[0] + o1[0] : o0[2] + o1[2], low_half ? o0[1] + o1[1] : o0[3] + o1[3], x_bar);
        return;
    }
    constexpr int kLast = kTotal - 1;
    uint32_t pb[2][4];
#pragma unroll
    for (int u = 0; u < 2; u++) ldsm_x4(sb + kOffPeerP + (r8 & 3) * kPeerPitch + mi * 16 + u * 64, pb[u]);
    uint32_t base = ring + (kLast % kStages) * kStageBytes + kPieceBytes + (mi >> 1) * 1024 + r8 * 128 + (((chunk & 7) ^ r8) << 4);
    pin32(base);
    mbar_wait_cluster(x_bar, 0);
    const float2 rem = lds_f2(x_addr);
    float q0[4] = {0.f, 0.f, 0.f, 0.f}, q1[4] = {0.f, 0.f, 0.f, 0.f};
    rest0 = fmaf(rem.x, f_rem0, rest0);
    rest1 = fmaf(rem.y, f_rem1, rest1);
    mbar_wait(bar_full + 16 * (kLast % kStages) + 8, (kLast / kStages) & 1);
    pv_piece(base, 2048, b[4 * kPre - 2], b[4 * kPre - 1], o0, o1);
    pv_piece(base + kPieceBytes / 2, 2048, pb[0], pb[1], q0, q1);
    const float y0 = fmaf(low_half ? q0[0] + q1[0] : q0[2] + q1[2], f_rem0,
                          fmaf(low_half ? o0[0] + o1[0] : o0[2] + o1[2], f_loc0, rest0));
    const float y1 = fmaf(low_half ? q0[1] + q1[1] : q0[3] + q1[3], f_rem1,
                          fmaf(low_half ? o0[1] + o1[1] : o0[3] + o1[3], f_loc1, rest1));
    const uint32_t pk = pack_bf16(y0, y1);
    asm volatile("st.global.u16 [%0], %1;" ::"l"(outp), "h"((uint16_t)pk) : "memory");
    asm volatile("st.global.u16 [%0 + 256], %1;" ::"l"(outp), "h"((uint16_t)(pk >> 16)) : "memory");
}

typedef CUresult (*EncodeTiledFn)(CUtensorMap*, CUtensorMapDataType, cuuint32_t, void*, const cuuint64_t*,
                                  const cuuint64_t*, const cuuint32_t*, const cuuint32_t*, CUtensorMapInterleave,
                                  CUtensorMapSwizzle, CUtensorMapL2promotion, CUtensorMapFloatOOBfill);

void encode_cache_map(EncodeTiledFn enc, CUtensorMap* map, const void* base, int halves) {
    const cuuint64_t dims[4] = {64, 8, 2, (cuuint64_t)kHeads * kC / 8};
    const cuuint64_t strides[3] = {256, 128, 2048};
    const cuuint32_t box[4] = {64, 8, (cuuint32_t)halves, 8};
    const cuuint32_t estr[4] = {1, 1, 1, 1};
    enc(map, CU_TENSOR_MAP_DATA_TYPE_BFLOAT16, 4, const_cast<void*>(base), dims, strides, box, estr,
        CU_TENSOR_MAP_INTERLEAVE_NONE, CU_TENSOR_MAP_SWIZZLE_128B, CU_TENSOR_MAP_L2_PROMOTION_NONE,
        CU_TENSOR_MAP_FLOAT_OOB_FILL_NONE);
}

}

extern "C" void kernel_launch(void* const* d_in, const int* in_sizes, int n_in, void* d_out, int out_size) {
    (void)in_sizes; (void)n_in; (void)out_size;
    static EncodeTiledFn enc = nullptr;
    static void* pace = nullptr;
    if (!enc) {
        void* fn = nullptr;
        cudaDriverEntryPointQueryResult qr;
        cudaGetDriverEntryPoint("cuTensorMapEncodeTiled", &fn, cudaEnableDefault, &qr);
        enc = (EncodeTiledFn)fn;
        cudaGetSymbolAddress(&pace, g_pace);
        cudaFuncSetAttribute(tree_attn_kernel, cudaFuncAttributeMaxDynamicSharedMemorySize, kSmemBytes);
    }
    Params prm;
    prm.k_raw = (const char*)d_in[1];
    prm.q = (const __nv_bfloat16*)d_in[0];
    prm.k_tree = (const __nv_bfloat16*)d_in[3];
    prm.v_tree = (const __nv_bfloat16*)d_in[4];
    prm.tree_mask = (const __nv_bfloat16*)d_in[5];
    prm.out = (__nv_bfloat16*)d_out;
    prm.pace = (unsigned int*)pace;
    encode_cache_map(enc, &prm.piece[0], d_in[1], 2);
    encode_cache_map(enc, &prm.piece[1], d_in[2], 2);
    encode_cache_map(enc, &prm.v_half, d_in[2], 1);
    tree_attn_kernel<<<kCtas, kThreads, kSmemBytes>>>(prm);
}
```

```cpp
#include <cuda_runtime.h>
#include <cuda_bf16.h>
#include <cuda.h>
#include <stdint.h>

namespace {

constexpr int kB = 8, kHq = 32, kHkv = 8, kC = 8192, kD = 128;
constexpr int kRep = kHq / kHkv;
constexpr int kHeads = kB * kHkv;
constexpr int kCtas = 2 * kHeads;
constexpr int kPieceBytes = 64 * kD * 2;
constexpr int kStageBytes = 2 * kPieceBytes;
constexpr int kStages = 4;
constexpr int kPassStages = 32;
constexpr int kTotal = 2 * kPassStages;
constexpr int kPre = 2;
constexpr int kGroupsPerCta = kC / 2 / 8;
constexpr int kConsumerWarps = 8;
constexpr int kThreads = 32 * (kConsumerWarps + 2);
constexpr int kPitch = kPassStages * 128 * 2 + 16;
constexpr int kPeerPitch = 64 * 2 + 16;
constexpr int kPrefetchBytes = 16384;
constexpr int kPaceTicks = kCtas * 2 * (kTotal - kStages);
constexpr int kPaceLead = (2 * kStages - 1) * kCtas + 232;
constexpr int kPaceStart = 10 * kCtas;
constexpr int kPaceLast = (2 * kTotal - 1) * kCtas + 48;
constexpr int kPacePatience = 400;

constexpr int kOffRing = 0;
constexpr int kOffP = kOffRing + kStages * kStageBytes;
constexpr int kOffPeerP = kOffP + kRep * kPitch;
constexpr int kOffQ = kOffPeerP + kRep * kPeerPitch;
constexpr int kOffX = kOffQ + kRep * kD * 2;
constexpr int kOffWmax = kOffX + 2048;
constexpr int kOffStatL = kOffWmax + 64;
constexpr int kOffStatR = kOffStatL + 64;
constexpr int kOffTree = kOffStatR + 64;
constexpr int kOffKt = kOffTree + 16;
constexpr int kOffVt = kOffKt + kD * 2;
constexpr int kOffMask = kOffVt + kD * 2;
constexpr int kOffPace = kOffMask + 16;
constexpr int kOffBar = kOffPace + 16;
constexpr int kSmemUsed = kOffBar + 8 * (3 * kStages + 2 + kConsumerWarps);
constexpr int kSmemBytes = kSmemUsed + 1024;
static_assert(kSmemBytes <= 232448, "shared memory");

constexpr float kScale = 0.08838834764831845f;
constexpr float kLog2e = 1.4426950408889634f;
constexpr uint32_t kNegInf2 = 0xff80ff80u;

__device__ unsigned int g_pace[32];

__device__ __forceinline__ uint32_t smem_u32(const void* p) { return (uint32_t)__cvta_generic_to_shared(p); }
__device__ __forceinline__ void mbar_init(uint32_t bar, int cnt) {
    asm volatile("mbarrier.init.shared::cta.b64 [%0], %1;" ::"r"(bar), "r"(cnt) : "memory");
}
__device__ __forceinline__ void mbar_expect_tx(uint32_t bar, uint32_t bytes) {
    asm volatile("mbarrier.arrive.expect_tx.shared::cta.b64 _, [%0], %1;" ::"r"(bar), "r"(bytes) : "memory");
}
__device__ __forceinline__ void mbar_arrive(uint32_t bar) {
    asm volatile("mbarrier.arrive.shared::cta.b64 _, [%0];" ::"r"(bar) : "memory");
}
__device__ __forceinline__ void mbar_wait(uint32_t bar, uint32_t parity) {
    asm volatile(
        "{\n"
        ".reg .pred p;\n"
        ".reg .u32 n;\n"
        "mov.u32 n, 0;\n"
        "WAIT_LOOP:\n"
        "mbarrier.try_wait.parity.shared::cta.b64 p, [%0], %1;\n"
        "@p bra WAIT_DONE;\n"
        "add.u32 n, n, 1;\n"
        "setp.lt.u32 p, n, 0x1000000;\n"
        "@p bra WAIT_LOOP;\n"
        "trap;\n"
        "WAIT_DONE:\n"
        "}\n" ::"r"(bar), "r"(parity) : "memory");
}
__device__ __forceinline__ void mbar_wait_cluster(uint32_t bar, uint32_t parity) {
    asm volatile(
        "{\n"
        ".reg .pred p;\n"
        ".reg .u32 n;\n"
        "mov.u32 n, 0;\n"
        "WAIT_LOOP:\n"
        "mbarrier.try_wait.parity.relaxed.cluster.shared::cta.b64 p, [%0], %1;\n"
        "@p bra WAIT_DONE;\n"
        "add.u32 n, n, 1;\n"
        "setp.lt.u32 p, n, 0x1000000;\n"
        "@p bra WAIT_LOOP;\n"
        "trap;\n"
        "WAIT_DONE:\n"
        "fence.acquire.sync_restrict::shared::cluster.cluster;\n"
        "}\n" ::"r"(bar), "r"(parity) : "memory");
}
__device__ __forceinline__ void tma_box(uint32_t dst, const CUtensorMap* map, int half, int group, uint32_t bar) {
    asm volatile(
        "cp.async.bulk.tensor.4d.shared::cluster.global.mbarrier::complete_tx::bytes [%0], [%1, {%3, %3, %4, %5}], [%2];"
        ::"r"(dst), "l"(map), "r"(bar), "r"(0), "r"(half), "r"(group) : "memory");
}
__device__ __forceinline__ void bulk_copy(uint32_t dst, const void* src, uint32_t bytes, uint32_t bar) {
    asm volatile("cp.async.bulk.shared::cluster.global.mbarrier::complete_tx::bytes [%0], [%1], %2, [%3];"
                 ::"r"(dst), "l"(src), "r"(bytes), "r"(bar) : "memory");
}
__device__ __forceinline__ bool elect_one() {
    uint32_t p;
    asm volatile("{\n.reg .pred p;\nelect.sync _|p, 0xffffffff;\nselp.u32 %0, 1, 0, p;\n}\n" : "=r"(p));
    return p != 0;
}
template <typename T> __device__ __forceinline__ void pin32(T& v) { asm volatile("" : "+r"(v)); }
template <typename T> __device__ __forceinline__ void pin64(T& v) { asm volatile("" : "+l"(v)); }
__device__ __forceinline__ void ldsm_x4(uint32_t addr, uint32_t (&r)[4]) {
    asm volatile("ldmatrix.sync.aligned.m8n8.x4.shared.b16 {%0,%1,%2,%3}, [%4];"
                 : "=r"(r[0]), "=r"(r[1]), "=r"(r[2]), "=r"(r[3]) : "r"(addr) : "memory");
}
__device__ __forceinline__ void ldsm_x4_t(uint32_t addr, uint32_t (&r)[4]) {
    asm volatile("ldmatrix.sync.aligned.m8n8.x4.trans.shared.b16 {%0,%1,%2,%3}, [%4];"
                 : "=r"(r[0]), "=r"(r[1]), "=r"(r[2]), "=r"(r[3]) : "r"(addr) : "memory");
}
__device__ __forceinline__ void stsm_x1_t(uint32_t addr, uint32_t v) {
    asm volatile("stmatrix.sync.aligned.m8n8.x1.trans.shared.b16 [%0], {%1};" ::"r"(addr), "r"(v) : "memory");
}
__device__ __forceinline__ void mma_bf16(float (&c)[4], const uint32_t (&a)[4], uint32_t b0, uint32_t b1) {
    asm volatile("mma.sync.aligned.m16n8k16.row.col.f32.bf16.bf16.f32 {%0,%1,%2,%3}, {%4,%5,%6,%7}, {%8,%9}, {%0,%1,%2,%3};"
                 : "+f"(c[0]), "+f"(c[1]), "+f"(c[2]), "+f"(c[3])
                 : "r"(a[0]), "r"(a[1]), "r"(a[2]), "r"(a[3]), "r"(b0), "r"(b1));
}
__device__ __forceinline__ uint32_t pack_bf16(float lo, float hi) {
    uint32_t r;
    asm("cvt.rn.bf16x2.f32 %0, %1, %2;" : "=r"(r) : "f"(hi), "f"(lo));
    return r;
}
__device__ __forceinline__ float bf_lo(uint32_t v) { return __uint_as_float(v << 16); }
__device__ __forceinline__ float bf_hi(uint32_t v) { return __uint_as_float(v & 0xffff0000u); }
__device__ __forceinline__ uint32_t max_bf16x2(uint32_t a, uint32_t b) {
    uint32_t r;
    asm("max.bf16x2 %0, %1, %2;" : "=r"(r) : "r"(a), "r"(b));
    return r;
}
__device__ __forceinline__ float round_bf16(float x) { return bf_lo(pack_bf16(x, 0.f)); }
__device__ __forceinline__ float exp_diff(float x, float m) {
    float r;
    asm("ex2.approx.ftz.f32 %0, %1;" : "=f"(r) : "f"((x - m) * kLog2e));
    return r;
}
__device__ __forceinline__ uint32_t map_to_cta(uint32_t addr, uint32_t cta) {
    uint32_t r;
    asm("mapa.shared::cluster.u32 %0, %1, %2;" : "=r"(r) : "r"(addr), "r"(cta));
    return r;
}
__device__ __forceinline__ void st_async_u4(uint32_t addr, const uint32_t (&v)[4], uint32_t bar) {
    asm volatile("st.async.weak.shared::cluster.mbarrier::complete_tx::bytes.v4.b32 [%0], {%1, %2, %3, %4}, [%5];"
                 ::"r"(addr), "r"(v[0]), "r"(v[1]), "r"(v[2]), "r"(v[3]), "r"(bar) : "memory");
}
__device__ __forceinline__ void st_async_f2(uint32_t addr, float a, float b, uint32_t bar) {
    asm volatile("st.async.weak.shared::cluster.mbarrier::complete_tx::bytes.v2.f32 [%0], {%1, %2}, [%3];"
                 ::"r"(addr), "f"(a), "f"(b), "r"(bar) : "memory");
}
__device__ __forceinline__ void consumer_sync() { asm volatile("bar.sync 1, 256;" ::: "memory"); }
__device__ __forceinline__ float2 lds_f2(uint32_t addr) {
    float2 v;
    asm volatile("ld.shared.v2.f32 {%0,%1}, [%2];" : "=f"(v.x), "=f"(v.y) : "r"(addr) : "memory");
    return v;
}
__device__ __forceinline__ float4 lds_f4(uint32_t addr) {
    float4 v;
    asm volatile("ld.shared.v4.f32 {%0,%1,%2,%3}, [%4];" : "=f"(v.x), "=f"(v.y), "=f"(v.z), "=f"(v.w) : "r"(addr) : "memory");
    return v;
}
__device__ __forceinline__ void lds_u4(uint32_t addr, uint32_t (&v)[4]) {
    asm volatile("ld.shared.v4.u32 {%0,%1,%2,%3}, [%4];" : "=r"(v[0]), "=r"(v[1]), "=r"(v[2]), "=r"(v[3]) : "r"(addr) : "memory");
}
__device__ __forceinline__ void sts_u4(uint32_t addr, const uint32_t (&v)[4]) {
    asm volatile("st.shared.v4.u32 [%0], {%1,%2,%3,%4};" ::"r"(addr), "r"(v[0]), "r"(v[1]), "r"(v[2]), "r"(v[3]) : "memory");
}
__device__ __forceinline__ void sts_f2(uint32_t addr, float a, float b) {
    asm volatile("st.shared.v2.f32 [%0], {%1,%2};" ::"r"(addr), "f"(a), "f"(b) : "memory");
}
__device__ __forceinline__ int lds_volatile(uint32_t addr) {
    int v;
    asm volatile("ld.volatile.shared.s32 %0, [%1];" : "=r"(v) : "r"(addr) : "memory");
    return v;
}
__device__ __forceinline__ void sts_volatile(uint32_t addr, int v) {
    asm volatile("st.volatile.shared.s32 [%0], %1;" ::"r"(addr), "r"(v) : "memory");
}

struct alignas(64) Params {
    const char* k_raw;
    const __nv_bfloat16 *q, *k_tree, *v_tree, *tree_mask;
    __nv_bfloat16* out;
    unsigned int* pace;
    CUtensorMap piece[2];
    CUtensorMap v_half;
};

__global__ void __cluster_dims__(2, 1, 1) __launch_bounds__(kThreads, 1)
tree_attn_kernel(const __grid_constant__ Params prm) {
    if (threadIdx.x == 0)
        asm volatile("cp.async.bulk.prefetch.L2.global [%0], %1;"
                     ::"l"(prm.k_raw + (size_t)blockIdx.x * (kGroupsPerCta * 2048)), "r"(kPrefetchBytes) : "memory");

    extern __shared__ uint8_t smem_raw[];
    const uint32_t sb = (smem_u32(smem_raw) + 1023u) & ~1023u;
    const uint32_t ring = sb + kOffRing;
    const uint32_t bar_full = sb + kOffBar;
    const uint32_t bar_empty = bar_full + 16 * kStages;
    const uint32_t bar_stat = bar_empty + 8 * kStages;
    const uint32_t bar_q = bar_stat + 8;
    const uint32_t bar_xo = bar_q + 8;
    const int warp = threadIdx.x >> 5, lane = threadIdx.x & 31;
    const int bh = blockIdx.x >> 1;
    const int rank = blockIdx.x & 1;
    const int group0 = blockIdx.x * kGroupsPerCta;

    if (warp == 0) {
        if (elect_one()) {
#pragma unroll
            for (int n = 0; n < 2 * kStages; n++) {
                mbar_init(bar_full + 8 * n, 1);
                mbar_expect_tx(bar_full + 8 * n, kPieceBytes);
                tma_box(ring + n * kPieceBytes, &prm.piece[0], 0, group0 + n * 8, bar_full + 8 * n);
                if (n == 0) {
                    mbar_init(bar_q, 1);
                    mbar_expect_tx(bar_q, kRep * kD * 2 + 2 * kD * 2 + 16);
                    bulk_copy(sb + kOffQ, prm.q + (size_t)bh * kRep * kD, kRep * kD * 2, bar_q);
                }
                if (n == 1) {
                    bulk_copy(sb + kOffKt, prm.k_tree + (size_t)bh * kD, kD * 2, bar_q);
                    bulk_copy(sb + kOffVt, prm.v_tree + (size_t)bh * kD, kD * 2, bar_q);
                    bulk_copy(sb + kOffMask, prm.tree_mask, 16, bar_q);
                }
            }
            asm volatile("prefetch.tensormap [%0];" ::"l"(&prm.piece[1]) : "memory");
            asm volatile("prefetch.tensormap [%0];" ::"l"(&prm.v_half) : "memory");
#pragma unroll
            for (int s = 0; s < kStages; s++) mbar_init(bar_empty + 8 * s, kConsumerWarps);
            mbar_init(bar_stat, 1);
#pragma unroll
            for (int u = 0; u < kConsumerWarps; u++) mbar_init(bar_xo + 8 * u, 1);
            mbar_expect_tx(bar_stat, kConsumerWarps * 8 + kRep * 64 * 2);
#pragma unroll
            for (int u = 0; u < kConsumerWarps; u++) mbar_expect_tx(bar_xo + 8 * u, 32 * 8);
            sts_volatile(sb + kOffPace, kPaceStart);
            sts_volatile(sb + kOffPace + 4, 0);
            asm volatile("fence.mbarrier_init.release.cluster;" ::: "memory");
        }
        __syncwarp();
    }
    __syncthreads();
    asm volatile("barrier.cluster.arrive.relaxed.aligned;" ::: "memory");

    if (warp == 0) {
        if (elect_one()) {
            unsigned int* pace = prm.pace;
            int s = 0, ph = 0, patience = kPacePatience;
#pragma unroll 1
            for (int i = kStages; i < kTotal; i++) {
                mbar_wait(bar_empty + 8 * s, ph);
                const int grp = group0 + (i & (kPassStages - 1)) * 16;
#pragma unroll
                for (int h = 0; h < 2; h++) {
                    const bool last = h == 1 && i == kTotal - 1;
                    const int need = last ? kPaceLast : (2 * i + h) * kCtas;
                    while (need > lds_volatile(sb + kOffPace) && patience > 0) { patience--; __nanosleep(20); }
                    if (patience > 0) patience = kPacePatience;
                    const uint32_t dst = ring + s * kStageBytes + h * kPieceBytes, bar = bar_full + 16 * s + 8 * h;
                    mbar_expect_tx(bar, kPieceBytes);
                    if (last) {
                        tma_box(dst, &prm.v_half, rank, grp + 8, bar);
                        tma_box(dst + kPieceBytes / 2, &prm.v_half, rank, (grp + 8) ^ kGroupsPerCta, bar);
                    } else {
                        tma_box(dst, &prm.piece[i >> 5], 0, grp + 8 * h, bar);
                    }
                    asm volatile("red.relaxed.gpu.global.inc.u32 [%0], %1;" ::"l"(pace), "r"(kPaceTicks - 1) : "memory");
                }
                if (++s == kStages) { s = 0; ph ^= 1; }
            }
            sts_volatile(sb + kOffPace + 4, 1);
        }
        __syncwarp();
        asm volatile("barrier.cluster.wait.aligned;" ::: "memory");
        return;
    }
    if (warp == 1) {
        asm volatile("barrier.cluster.wait.aligned;" ::: "memory");
        if (elect_one()) {
            const unsigned int* pace = prm.pace;
            int limit = kPaceStart;
#pragma unroll 1
            for (int n = 0; n < (1 << 20) && lds_volatile(sb + kOffPace + 4) == 0; n++) {
                unsigned int ticks;
                asm volatile("ld.relaxed.gpu.global.u32 %0, [%1];" : "=r"(ticks) : "l"(pace) : "memory");
                const int v = kPaceLead + (int)ticks;
                if (v > limit) { limit = v; sts_volatile(sb + kOffPace, v); }
                if (limit >= kPaceLast) break;
                __nanosleep(100);
            }
        }
        return;
    }

    const int w = warp - 2;
    const int g = lane >> 2, t = lane & 3;
    const int mi = lane >> 3, r8 = lane & 7;
    const bool low_half = t < 2;
    const bool keeper = (w >> 2) == rank;
    uint32_t k_off = ring + (2 * w + (mi & 1)) * 2048 + r8 * 128 + (((mi >> 1) ^ r8) << 4);
    const int chunk = 2 * w + (mi & 1);
    uint32_t v_off = ring + (mi >> 1) * 2048 + (chunk >> 3) * 1024 + r8 * 128 + (((chunk & 7) ^ r8) << 4);
    uint32_t s_addr = sb + kOffP + (r8 & 3) * kPitch + (16 * w + 8 * (r8 >> 2)) * 2;
    uint32_t p_addr = sb + kOffP + (r8 & 3) * kPitch + mi * 16;
    pin32(k_off);
    pin32(v_off);
    const int h0 = 2 * (t & 1);
    const int d_own = 16 * w + g + 8 * (t >> 1);
    __nv_bfloat16* outp = prm.out + (size_t)(bh * kRep + h0) * kD + d_own;
    pin64(outp);
    uint32_t x_addr = sb + kOffX + (w * 32 + lane) * 8;
    uint32_t x_bar = bar_xo + 8 * w;
    if (!keeper) { x_addr = map_to_cta(x_addr, rank ^ 1); x_bar = map_to_cta(x_bar, rank ^ 1); }
    pin32(x_addr);
    pin32(x_bar);

    asm volatile("barrier.cluster.wait.aligned;" ::: "memory");
    mbar_wait(bar_q, 0);
    uint32_t qf[4][4];
#pragma unroll
    for (int j = 0; j < 4; j++) ldsm_x4(sb + kOffQ + (r8 & 3) * (kD * 2) + mi * 16 + j * 64, qf[j]);
    if (w < kRep) {
        uint2 qa, ka;
        uint16_t mk16;
        asm volatile("ld.shared.v2.u32 {%0,%1}, [%2];" : "=r"(qa.x), "=r"(qa.y) : "r"(sb + kOffQ + w * (kD * 2) + lane * 8) : "memory");
        asm volatile("ld.shared.v2.u32 {%0,%1}, [%2];" : "=r"(ka.x), "=r"(ka.y) : "r"(sb + kOffKt + lane * 8) : "memory");
        asm volatile("ld.shared.u16 %0, [%1];" : "=h"(mk16) : "r"(sb + kOffMask + (bh / kHkv) * 2) : "memory");
        float sc = bf_lo(qa.x) * bf_lo(ka.x);
        sc = fmaf(bf_hi(qa.x), bf_hi(ka.x), sc);
        sc = fmaf(bf_lo(qa.y), bf_lo(ka.y), sc);
        sc = fmaf(bf_hi(qa.y), bf_hi(ka.y), sc);
#pragma unroll
        for (int o = 16; o > 0; o >>= 1) sc += __shfl_xor_sync(0xffffffffu, sc, o);
        sc = round_bf16(round_bf16(sc) * kScale);
        sc = round_bf16(sc + round_bf16(round_bf16(1.0f - bf_lo(mk16)) * -1000000000.0f));
        if (lane == 0) asm volatile("st.shared.f32 [%0], %1;" ::"r"(sb + kOffTree + 4 * w), "f"(sc) : "memory");
    }

    int s = 0, ph = 0;
    uint32_t mx = kNegInf2;
#pragma unroll 1
    for (int i = 0; i < kPassStages; i++) {
        uint32_t base = k_off + s * kStageBytes;
        pin32(base);
        mbar_wait(bar_full + 16 * s + 8 * (w >> 2), ph);
        float c0[4] = {0.f, 0.f, 0.f, 0.f}, c1[4] = {0.f, 0.f, 0.f, 0.f};
        uint32_t a[8][4];
#pragma unroll
        for (int j = 0; j < 8; j++) ldsm_x4((base ^ ((j & 3) << 5)) + (j >> 2) * 1024, a[j]);
#pragma unroll
        for (int j = 0; j < 8; j += 2) {
            mma_bf16(c0, a[j], qf[j >> 1][0], qf[j >> 1][1]);
            mma_bf16(c1, a[j + 1], qf[j >> 1][2], qf[j >> 1][3]);
        }
        if (lane == 0) mbar_arrive(bar_empty + 8 * s);
        const float x0 = low_half ? c0[0] + c1[0] : c0[2] + c1[2];
        const float x1 = low_half ? c0[1] + c1[1] : c0[3] + c1[3];
        const uint32_t raw = pack_bf16(x0, x1);
        const uint32_t sc = pack_bf16(bf_lo(raw) * kScale, bf_hi(raw) * kScale);
        mx = max_bf16x2(mx, sc);
        stsm_x1_t(s_addr, sc);
        s_addr += 256;
        if (++s == kStages) { s = 0; ph ^= 1; }
    }

    {
#pragma unroll
        for (int o = 2; o < 32; o <<= 1) mx = max_bf16x2(mx, __shfl_xor_sync(0xffffffffu, mx, o));
        if (lane < 2) asm volatile("st.shared.u32 [%0], %1;" ::"r"(sb + kOffWmax + w * 8 + lane * 4), "r"(mx) : "memory");
        consumer_sync();
        const int head = w >> 1;
        uint32_t m2;
        asm volatile("ld.shared.u32 %0, [%1];" : "=r"(m2) : "r"(sb + kOffWmax + r8 * 8 + (head >> 1) * 4) : "memory");
#pragma unroll
        for (int o = 1; o < 8; o <<= 1) m2 = max_bf16x2(m2, __shfl_xor_sync(0xffffffffu, m2, o));
        const float m = (head & 1) ? bf_hi(m2) : bf_lo(m2);
        float sum = 0.f;
        uint32_t addr = sb + kOffP + head * kPitch + (w & 1) * (kPassStages * 128) + lane * 16;
        uint32_t v[4];
#pragma unroll 2
        for (int i = 0; i < kPassStages / 4; i++) {
            lds_u4(addr, v);
#pragma unroll
            for (int j = 0; j < 4; j++) {
                const float e0 = exp_diff(bf_lo(v[j]), m), e1 = exp_diff(bf_hi(v[j]), m);
                sum += e0 + e1;
                v[j] = pack_bf16(e0, e1);
            }
            sts_u4(addr, v);
            addr += 512;
        }
        const uint32_t peer_stat = map_to_cta(bar_stat, rank ^ 1);
        if ((w & 1) && lane >= 24)
            st_async_u4(map_to_cta(sb + kOffPeerP + head * kPeerPitch + (lane - 24) * 16, rank ^ 1), v, peer_stat);
#pragma unroll
        for (int o = 16; o > 0; o >>= 1) sum += __shfl_xor_sync(0xffffffffu, sum, o);
        if (lane == 0) {
            sts_f2(sb + kOffStatL + w * 8, m, sum);
            st_async_f2(map_to_cta(sb + kOffStatR + w * 8, rank ^ 1), m, sum, peer_stat);
        }
        consumer_sync();
    }

    float o0[4] = {0.f, 0.f, 0.f, 0.f}, o1[4] = {0.f, 0.f, 0.f, 0.f};
    float f_loc0 = 0.f, f_loc1 = 0.f, f_rem0 = 0.f, f_rem1 = 0.f, rest0 = 0.f, rest1 = 0.f;
    auto pv_piece = [&](uint32_t base, uint32_t step, const uint32_t (&b0)[4], const uint32_t (&b1)[4],
                        float (&c0)[4], float (&c1)[4]) {
        uint32_t a[4][4];
#pragma unroll
        for (int j = 0; j < 4; j++) ldsm_x4_t(base + j * step, a[j]);
        mma_bf16(c0, a[0], b0[0], b0[1]);
        mma_bf16(c1, a[1], b0[2], b0[3]);
        mma_bf16(c0, a[2], b1[0], b1[1]);
        mma_bf16(c1, a[3], b1[2], b1[3]);
    };
#pragma unroll 1
    for (int i = 0; i < kPassStages - kPre; i++) {
        uint32_t b[4][4];
#pragma unroll
        for (int u = 0; u < 4; u++) ldsm_x4(p_addr + u * 64, b[u]);
        p_addr += 256;
        if (i == 8 && keeper) {
            mbar_wait_cluster(bar_stat, 0);
            const float4 la = lds_f4(sb + kOffStatL + h0 * 16), lb = lds_f4(sb + kOffStatL + h0 * 16 + 16);
            const float4 ra = lds_f4(sb + kOffStatR + h0 * 16), rb = lds_f4(sb + kOffStatR + h0 * 16 + 16);
            const float2 st = lds_f2(sb + kOffTree + h0 * 4);
            uint16_t vt16;
            asm volatile("ld.shared.u16 %0, [%1];" : "=h"(vt16) : "r"(sb + kOffVt + d_own * 2) : "memory");
            const float vt = bf_lo(vt16);
            {
                const float m = fmaxf(fmaxf(la.x, ra.x), st.x);
                const float el = exp_diff(la.x, m), er = exp_diff(ra.x, m), et = exp_diff(st.x, m);
                const float inv = __frcp_rn(el * (la.y + la.w) + er * (ra.y + ra.w) + et);
                f_loc0 = el * inv; f_rem0 = er * inv; rest0 = et * inv * vt;
            }
            {
                const float m = fmaxf(fmaxf(lb.x, rb.x), st.y);
                const float el = exp_diff(lb.x, m), er = exp_diff(rb.x, m), et = exp_diff(st.y, m);
                const float inv = __frcp_rn(el * (lb.y + lb.w) + er * (rb.y + rb.w) + et);
                f_loc1 = el * inv; f_rem1 = er * inv; rest1 = et * inv * vt;
            }
        }
        uint32_t base = v_off + s * kStageBytes;
        pin32(base);
        mbar_wait(bar_full + 16 * s, ph);
        pv_piece(base, 4096, b[0], b[1], o0, o1);
        mbar_wait(bar_full + 16 * s + 8, ph);
        pv_piece(base + kPieceBytes, 4096, b[2], b[3], o0, o1);
        if (lane == 0) mbar_arrive(bar_empty + 8 * s);
        if (++s == kStages) { s = 0; ph ^= 1; }
    }
    uint32_t b[4 * kPre][4];
#pragma unroll
    for (int u = 0; u < 4 * kPre; u++) ldsm_x4(p_addr + u * 64, b[u]);
#pragma unroll
    for (int n = 0; n < 2 * kPre - 1; n++) {
        const int i = kTotal - kPre + (n >> 1);
        mbar_wait(bar_full + 16 * (i % kStages) + 8 * (n & 1), (i / kStages) & 1);
        pv_piece(v_off + (i % kStages) * kStageBytes + (n & 1) * kPieceBytes, 4096, b[2 * n], b[2 * n + 1], o0, o1);
        if ((n & 1) && i + kStages < kTotal && lane == 0) mbar_arrive(bar_empty + 8 * (i % kStages));
    }
    if (!keeper) {
        st_async_f2(x_addr, low_half ? o0[0] + o1[0] : o0[2] + o1[2], low_half ? o0[1] + o1[1] : o0[3] + o1[3], x_bar);
        return;
    }
    constexpr int kLast = kTotal - 1;
    uint32_t pb[2][4];
#pragma unroll
    for (int u = 0; u < 2; u++) ldsm_x4(sb + kOffPeerP + (r8 & 3) * kPeerPitch + mi * 16 + u * 64, pb[u]);
    uint32_t base = ring + (kLast % kStages) * kStageBytes + kPieceBytes + (mi >> 1) * 1024 + r8 * 128 + (((chunk & 7) ^ r8) << 4);
    pin32(base);
    mbar_wait_cluster(x_bar, 0);
    const float2 rem = lds_f2(x_addr);
    float q0[4] = {0.f, 0.f, 0.f, 0.f}, q1[4] = {0.f, 0.f, 0.f, 0.f};
    rest0 = fmaf(rem.x, f_rem0, rest0);
    rest1 = fmaf(rem.y, f_rem1, rest1);
    mbar_wait(bar_full + 16 * (kLast % kStages) + 8, (kLast / kStages) & 1);
    pv_piece(base, 2048, b[4 * kPre - 2], b[4 * kPre - 1], o0, o1);
    pv_piece(base + kPieceBytes / 2, 2048, pb[0], pb[1], q0, q1);
    const float y0 = fmaf(low_half ? q0[0] + q1[0] : q0[2] + q1[2], f_rem0,
                          fmaf(low_half ? o0[0] + o1[0] : o0[2] + o1[2], f_loc0, rest0));
    const float y1 = fmaf(low_half ? q0[1] + q1[1] : q0[3] + q1[3], f_rem1,
                          fmaf(low_half ? o0[1] + o1[1] : o0[3] + o1[3], f_loc1, rest1));
    const uint32_t pk = pack_bf16(y0, y1);
    asm volatile("st.global.u16 [%0], %1;" ::"l"(outp), "h"((uint16_t)pk) : "memory");
    asm volatile("st.global.u16 [%0 + 256], %1;" ::"l"(outp), "h"((uint16_t)(pk >> 16)) : "memory");
}

typedef CUresult (*EncodeTiledFn)(CUtensorMap*, CUtensorMapDataType, cuuint32_t, void*, const cuuint64_t*,
                                  const cuuint64_t*, const cuuint32_t*, const cuuint32_t*, CUtensorMapInterleave,
                                  CUtensorMapSwizzle, CUtensorMapL2promotion, CUtensorMapFloatOOBfill);

void encode_cache_map(EncodeTiledFn enc, CUtensorMap* map, const void* base, int halves) {
    const cuuint64_t dims[4] = {64, 8, 2, (cuuint64_t)kHeads * kC / 8};
    const cuuint64_t strides[3] = {256, 128, 2048};
    const cuuint32_t box[4] = {64, 8, (cuuint32_t)halves, 8};
    const cuuint32_t estr[4] = {1, 1, 1, 1};
    enc(map, CU_TENSOR_MAP_DATA_TYPE_BFLOAT16, 4, const_cast<void*>(base), dims, strides, box, estr,
        CU_TENSOR_MAP_INTERLEAVE_NONE, CU_TENSOR_MAP_SWIZZLE_128B, CU_TENSOR_MAP_L2_PROMOTION_NONE,
        CU_TENSOR_MAP_FLOAT_OOB_FILL_NONE);
}

}

extern "C" void kernel_launch(void* const* d_in, const int* in_sizes, int n_in, void* d_out, int out_size) {
    (void)in_sizes; (void)n_in; (void)out_size;
    static EncodeTiledFn enc = nullptr;
    static void* pace = nullptr;
    if (!enc) {
        void* fn = nullptr;
        cudaDriverEntryPointQueryResult qr;
        cudaGetDriverEntryPoint("cuTensorMapEncodeTiled", &fn, cudaEnableDefault, &qr);
        enc = (EncodeTiledFn)fn;
        cudaGetSymbolAddress(&pace, g_pace);
        cudaFuncSetAttribute(tree_attn_kernel, cudaFuncAttributeMaxDynamicSharedMemorySize, kSmemBytes);
    }
    Params prm;
    prm.k_raw = (const char*)d_in[1];
    prm.q = (const __nv_bfloat16*)d_in[0];
    prm.k_tree = (const __nv_bfloat16*)d_in[3];
    prm.v_tree = (const __nv_bfloat16*)d_in[4];
    prm.tree_mask = (const __nv_bfloat16*)d_in[5];
    prm.out = (__nv_bfloat16*)d_out;
    prm.pace = (unsigned int*)pace;
    encode_cache_map(enc, &prm.piece[0], d_in[1], 2);
    encode_cache_map(enc, &prm.piece[1], d_in[2], 2);
    encode_cache_map(enc, &prm.v_half, d_in[2], 1);
    tree_attn_kernel<<<kCtas, kThreads, kSmemBytes>>>(prm);
}
```
